```python
import torch

def _softmax(x, axis=-1):
    return torch.softmax(x, dim=axis)
def _gelu(x):
    return torch.nn.functional.gelu(x, approximate="tanh")
def _silu(x):
    return torch.nn.functional.silu(x)
def _sigmoid(x):
    return torch.sigmoid(x)
def _layernorm(x, axis=-1, eps=1e-5):
    m = x.mean(dim=axis, keepdim=True)
    v = x.var(dim=axis, keepdim=True, unbiased=False)
    return (x - m) / torch.sqrt(v + eps)
def _scatter_add(tgt, idx, src, axis=0):
    return tgt.clone().index_add_(axis, idx, src)
def _segment_sum(src, seg, n):
    out = torch.zeros((n,) + src.shape[1:], dtype=src.dtype)
    return out.index_add_(0, seg, src)
def _pad(x, pw):
    flat = tuple(v for pair in reversed(pw) for v in pair)
    return torch.nn.functional.pad(x, flat)

kernel_name = 'concat_heads__sliding_block_cached__sliding_block_cached__decode'

def setup_inputs():

    _w = (lambda a: (lambda t: t.to(torch.bfloat16) if t.is_floating_point() else t)(torch.as_tensor(a)))
    def _A_setup():
        B, Sq, D = 4, 1, 640
        Hq, Hkv, Sk, Dh = 32, 32, 8192, 128
        assert Hq % Hkv == 0, (Hq, Hkv)
        return {
            "x": _w((lambda *s: torch.randn(*s, dtype=torch.bfloat16) * 0.8)(B, Sq, D)),
            "k_cache": _w((lambda *s: torch.randn(*s, dtype=torch.bfloat16) * 0.8)(B, Hkv, Sk, Dh)),
            "v_cache": _w((lambda *s: torch.randn(*s, dtype=torch.bfloat16) * 0.05)(B, Hkv, Sk, Dh)),
            "wq": _w((lambda *s: torch.randn(*s, dtype=torch.bfloat16) * 0.8)(D, Hq * Dh) * (D ** -0.5)),
            "wo": _w((lambda *s: torch.randn(*s, dtype=torch.bfloat16) * 0.05)(Hq * Dh, D) * ((Hq * Dh) ** -0.5)),
        }
    _A_in = _A_setup()

    def _B_setup():
        B, Sq, D = 4, 1, 640
        Hq, Hkv, Sk, Dh = 32, 32, 8192, 128
        assert Hq % Hkv == 0, (Hq, Hkv)
        return {
            "x": _w((lambda *s: torch.randn(*s, dtype=torch.bfloat16) * 0.8)(B, Sq, D)),
            "k_cache": _w((lambda *s: torch.randn(*s, dtype=torch.bfloat16) * 0.8)(B, Hkv, Sk, Dh)),
            "v_cache": _w((lambda *s: torch.randn(*s, dtype=torch.bfloat16) * 0.05)(B, Hkv, Sk, Dh)),
            "wq": _w((lambda *s: torch.randn(*s, dtype=torch.bfloat16) * 0.8)(D, Hq * Dh) * (D ** -0.5)),
            "wo": _w((lambda *s: torch.randn(*s, dtype=torch.bfloat16) * 0.05)(Hq * Dh, D) * ((Hq * Dh) ** -0.5)),
        }
    _B_in = _B_setup()

    return {
        "A_x": _A_in["x"],
        "A_k_cache": _A_in["k_cache"],
        "A_v_cache": _A_in["v_cache"],
        "A_wq": _A_in["wq"],
        "A_wo": _A_in["wo"],
        "B_x": _B_in["x"],
        "B_k_cache": _B_in["k_cache"],
        "B_v_cache": _B_in["v_cache"],
        "B_wq": _B_in["wq"],
        "B_wo": _B_in["wo"],
    }

def reference(A_x, A_k_cache, A_v_cache, A_wq, A_wo, B_x, B_k_cache, B_v_cache, B_wq, B_wo):
    def _A_ref(x, k_cache, v_cache, wq, wo):
        B, Sq, D = x.shape
        Hq, Dh = 32, 128
        Hkv, Sk = k_cache.shape[1], k_cache.shape[2]
        W = min(4096, max(256, Sk // 4))
        rep = Hq // Hkv
        q = (lambda x, *d: x.permute(*d))((x @ wq).reshape(B, Sq, Hq, Dh), 0, 2, 1, 3)
        k = (lambda x, n, axis: torch.repeat_interleave(x, n, dim=axis))(k_cache[:, :, Sk - W:, :], rep, axis=1)
        v = (lambda x, n, axis: torch.repeat_interleave(x, n, dim=axis))(v_cache[:, :, Sk - W:, :], rep, axis=1)
        scores = torch.einsum("bhqd,bhkd->bhqk", q, k) * (Dh ** -0.5)
        p = _softmax(scores, axis=-1)
        o = torch.einsum("bhqk,bhkd->bhqd", p, v)
        return (lambda x, *d: x.permute(*d))(o, 0, 2, 1, 3).reshape(B, Sq, Hq * Dh) @ wo

    def _B_ref(x, k_cache, v_cache, wq, wo):
        B, Sq, D = x.shape
        Hq, Dh = 32, 128
        Hkv, Sk = k_cache.shape[1], k_cache.shape[2]
        W = min(4096, max(256, Sk // 4))
        rep = Hq // Hkv
        q = (lambda x, *d: x.permute(*d))((x @ wq).reshape(B, Sq, Hq, Dh), 0, 2, 1, 3)
        k = (lambda x, n, axis: torch.repeat_interleave(x, n, dim=axis))(k_cache[:, :, Sk - W:, :], rep, axis=1)
        v = (lambda x, n, axis: torch.repeat_interleave(x, n, dim=axis))(v_cache[:, :, Sk - W:, :], rep, axis=1)
        scores = torch.einsum("bhqd,bhkd->bhqk", q, k) * (Dh ** -0.5)
        p = _softmax(scores, axis=-1)
        o = torch.einsum("bhqk,bhkd->bhqd", p, v)
        return (lambda x, *d: x.permute(*d))(o, 0, 2, 1, 3).reshape(B, Sq, Hq * Dh) @ wo

    a = _A_ref(A_x, A_k_cache, A_v_cache, A_wq, A_wo)
    b = _B_ref(B_x, B_k_cache, B_v_cache, B_wq, B_wo)
    return torch.concatenate([a, b], axis=-1)
```

```cpp
#include <cuda_runtime.h>
#include <cuda_bf16.h>
#include <cuda.h>
#include <stdint.h>

namespace {

constexpr int kB = 4, kD = 640, kH = 32, kS = 8192, kDH = 128, kW = 2048;
constexpr int kNSlot = 12;
constexpr int kTileBytes = 16384;
constexpr int kNumWqTiles = 10, kNumWoTiles = 10;
constexpr int kTilesPerUnit = 64;
constexpr int kNumTiles = kNumWqTiles + 2 * kTilesPerUnit + kNumWoTiles;
constexpr int kConsumerThreads = 256;
constexpr int kThreads = kConsumerThreads + 32;
constexpr int kNumCtas = 128;

struct Params {
    CUtensorMap k[2], v[2], wq[2], wo[2];
    const __nv_bfloat16* x[2];
    __nv_bfloat16* out;
};

constexpr int kOffRing = 0;
constexpr int kOffScores = kNSlot * kTileBytes;
constexpr int kOffP = kOffScores + 2048 * 4;
constexpr int kOffORed = kOffP + 2 * 2048 * 2;
constexpr int kOffX = kOffORed + 8 * 128 * 4;
constexpr int kOffQ = kOffX + 2 * 640 * 2;
constexpr int kOffO = kOffQ + 2 * 128 * 2;
constexpr int kOffRed = kOffO + 2 * 128 * 2;
constexpr int kOffFlag = kOffRed + 16 * 4;
constexpr int kOffBar = kOffFlag + 16;
constexpr int kSmemBytes = kOffBar + 2 * kNSlot * 8;
constexpr int kSmemAlloc = kSmemBytes + 1024;

__device__ float g_acc[2 * kB * kD];
__device__ unsigned int g_count;

__device__ __forceinline__ uint32_t smem_u32(const void* p) {
    return (uint32_t)__cvta_generic_to_shared(p);
}
__device__ __forceinline__ void mbar_init(uint32_t bar, uint32_t count) {
    asm volatile("mbarrier.init.shared::cta.b64 [%0], %1;" ::"r"(bar), "r"(count) : "memory");
}
__device__ __forceinline__ void mbar_expect_tx(uint32_t bar, uint32_t bytes) {
    asm volatile("mbarrier.arrive.expect_tx.shared::cta.b64 _, [%0], %1;" ::"r"(bar), "r"(bytes) : "memory");
}
__device__ __forceinline__ void mbar_arrive(uint32_t bar) {
    asm volatile("mbarrier.arrive.shared::cta.b64 _, [%0];" ::"r"(bar) : "memory");
}
__device__ __forceinline__ bool mbar_try_wait(uint32_t bar, uint32_t parity) {
    uint32_t ok;
    asm volatile(
        "{\n\t.reg .pred p;\n\t"
        "mbarrier.try_wait.parity.shared::cta.b64 p, [%1], %2;\n\t"
        "selp.u32 %0, 1, 0, p;\n\t}"
        : "=r"(ok) : "r"(bar), "r"(parity) : "memory");
    return ok != 0;
}
__device__ __forceinline__ void mbar_wait(uint32_t bar, uint32_t parity) {
    uint32_t spins = 0;
    while (!mbar_try_wait(bar, parity)) {
        if (++spins > (1u << 24)) __trap();
    }
}
__device__ __forceinline__ void tma_load_2d(uint32_t dst, const CUtensorMap* map, int c0, int c1,
                                            uint32_t bar, uint64_t policy) {
    asm volatile(
        "cp.async.bulk.tensor.2d.shared::cluster.global.mbarrier::complete_tx::bytes.L2::cache_hint "
        "[%0], [%1, {%3, %4}], [%2], %5;"
        ::"r"(dst), "l"(reinterpret_cast<uint64_t>(map)), "r"(bar), "r"(c0), "r"(c1), "l"(policy)
        : "memory");
}
__device__ __forceinline__ void ldsm_x4(uint32_t addr, uint32_t& r0, uint32_t& r1, uint32_t& r2, uint32_t& r3) {
    asm volatile("ldmatrix.sync.aligned.m8n8.x4.shared.b16 {%0,%1,%2,%3}, [%4];"
                 : "=r"(r0), "=r"(r1), "=r"(r2), "=r"(r3) : "r"(addr) : "memory");
}
__device__ __forceinline__ void ldsm_x4_t(uint32_t addr, uint32_t& r0, uint32_t& r1, uint32_t& r2, uint32_t& r3) {
    asm volatile("ldmatrix.sync.aligned.m8n8.x4.trans.shared.b16 {%0,%1,%2,%3}, [%4];"
                 : "=r"(r0), "=r"(r1), "=r"(r2), "=r"(r3) : "r"(addr) : "memory");
}
__device__ __forceinline__ void mma16816(float (&c)[4], uint32_t a0, uint32_t a1, uint32_t a2, uint32_t a3,
                                         uint32_t b0, uint32_t b1) {
    asm volatile(
        "mma.sync.aligned.m16n8k16.row.col.f32.bf16.bf16.f32 {%0,%1,%2,%3}, {%4,%5,%6,%7}, {%8,%9}, {%0,%1,%2,%3};"
        : "+f"(c[0]), "+f"(c[1]), "+f"(c[2]), "+f"(c[3])
        : "r"(a0), "r"(a1), "r"(a2), "r"(a3), "r"(b0), "r"(b1));
}
__device__ __forceinline__ void consumer_sync() {
    asm volatile("bar.sync 1, 256;" ::: "memory");
}
__device__ __forceinline__ uint32_t lds32(uint32_t addr) {
    uint32_t v;
    asm volatile("ld.shared.b32 %0, [%1];" : "=r"(v) : "r"(addr) : "memory");
    return v;
}

__global__ void __launch_bounds__(kThreads, 1)
fused_decode_kernel(const __grid_constant__ Params prm) {
    extern __shared__ unsigned char smem_raw[];
    const uint32_t raw = smem_u32(smem_raw);
    const uint32_t base = (raw + 1023u) & ~1023u;
    unsigned char* sm = smem_raw + (base - raw);

    const int tid = threadIdx.x;
    const int warp = tid >> 5, lane = tid & 31;
    const int blk = blockIdx.x;
    const int prob = blk >> 6;
    const int h = (blk & 63) >> 1;
    const int bp = blk & 1;

    const uint32_t bar_full = base + kOffBar;
    const uint32_t bar_empty = bar_full + kNSlot * 8;

    if (tid == 0) {
        for (int i = 0; i < kNSlot; i++) {
            mbar_init(bar_full + i * 8, 1);
            mbar_init(bar_empty + i * 8, 4);
        }
        asm volatile("fence.mbarrier_init.release.cluster;" ::: "memory");
        asm volatile("fence.proxy.async.shared::cta;" ::: "memory");
    }
    __syncthreads();

    if (warp == 8) {
        if (lane == 0) {
            uint64_t pol_stream, pol_norm;
            asm volatile("createpolicy.fractional.L2::evict_first.b64 %0, 1.0;" : "=l"(pol_stream));
            asm volatile("createpolicy.fractional.L2::evict_normal.b64 %0, 1.0;" : "=l"(pol_norm));
            const CUtensorMap* mk = &prm.k[prob];
            const CUtensorMap* mv = &prm.v[prob];
            const CUtensorMap* mq = &prm.wq[prob];
            const CUtensorMap* mo = &prm.wo[prob];
            for (int i = 0; i < kNumTiles; i++) {
                const int slot = i % kNSlot;
                const uint32_t full = bar_full + slot * 8;
                if (i >= kNSlot) mbar_wait(bar_empty + slot * 8, ((i / kNSlot) - 1) & 1);
                const uint32_t dst = base + kOffRing + slot * kTileBytes;
                mbar_expect_tx(full, kTileBytes);
                if (i < kNumWqTiles) {
                    tma_load_2d(dst, mq, h * kDH + (i & 1) * 64, (i >> 1) * 128, full, pol_norm);
                } else if (i < kNumWqTiles + 2 * kTilesPerUnit) {
                    const int r = i - kNumWqTiles;
                    const int u = r >> 6, j = r & 63;
                    const int b = 2 * bp + u;
                    const int row = (b * kH + h) * kS + (kS - kW) + (j & 31) * 64;
                    const CUtensorMap* m = (j < 32) ? mk : mv;
                    tma_load_2d(dst, m, 0, row, full, pol_stream);
                    tma_load_2d(dst + 8192, m, 64, row, full, pol_stream);
                } else {
                    const int c = i - (kNumWqTiles + 2 * kTilesPerUnit);
                    tma_load_2d(dst, mo, c * 64, h * kDH, full, pol_norm);
                }
            }
        }
        return;
    }

    const int grp = warp >> 2, wi = warp & 3;
    const int g = lane >> 2, t = lane & 3;
    const int mi = lane >> 3, l8 = lane & 7;

    float* scores_s = reinterpret_cast<float*>(sm + kOffScores);
    __nv_bfloat16* p_s = reinterpret_cast<__nv_bfloat16*>(sm + kOffP);
    float* ored_s = reinterpret_cast<float*>(sm + kOffORed);
    __nv_bfloat16* q_s = reinterpret_cast<__nv_bfloat16*>(sm + kOffQ);
    __nv_bfloat16* o_s = reinterpret_cast<__nv_bfloat16*>(sm + kOffO);
    float* red_s = reinterpret_cast<float*>(sm + kOffRed);
    volatile unsigned int* flag_s = reinterpret_cast<volatile unsigned int*>(sm + kOffFlag);

    if (tid < 160) {
        const uint4* src = reinterpret_cast<const uint4*>(prm.x[prob] + (size_t)(2 * bp) * kD);
        reinterpret_cast<uint4*>(sm + kOffX)[tid] = __ldg(src + tid);
    }
    consumer_sync();

    auto wait_full = [&](int i) { mbar_wait(bar_full + (i % kNSlot) * 8, (i / kNSlot) & 1); };
    auto release = [&](int i) {
        __syncwarp();
        if (lane == 0) mbar_arrive(bar_empty + (i % kNSlot) * 8);
    };

    const uint32_t w_lane_off = (uint32_t)((l8 + ((mi >> 1) << 3)) * 128 + (((2 * wi + (mi & 1)) ^ l8) << 4));
    const uint32_t k_row_off = (uint32_t)((16 * wi + l8 + ((mi & 1) << 3)) * 128);
    const uint32_t v_row_off = (uint32_t)((16 * wi + l8 + ((mi >> 1) << 3)) * 128);

    {
        float acc[4] = {0.f, 0.f, 0.f, 0.f};
        const uint32_t xb = base + kOffX + (uint32_t)((g & 1) * kD * 2 + t * 4);
#pragma unroll 1
        for (int kb = 0; kb < 5; kb++) {
            const int i = 2 * kb + grp;
            wait_full(i);
            const uint32_t tile = base + kOffRing + (i % kNSlot) * kTileBytes + w_lane_off;
#pragma unroll
            for (int s = 0; s < 8; s++) {
                uint32_t a0, a1, a2, a3;
                ldsm_x4_t(tile + s * 2048, a0, a1, a2, a3);
                uint32_t b0 = lds32(xb + (kb * 128 + s * 16) * 2);
                uint32_t b1 = lds32(xb + (kb * 128 + s * 16 + 8) * 2);
                mma16816(acc, a0, a1, a2, a3, b0, b1);
            }
            release(i);
        }
        if (t == 0) {
            const int d = grp * 64 + wi * 16 + g;
            q_s[d] = __float2bfloat16(acc[0]);
            q_s[128 + d] = __float2bfloat16(acc[1]);
            q_s[d + 8] = __float2bfloat16(acc[2]);
            q_s[128 + d + 8] = __float2bfloat16(acc[3]);
        }
    }
    consumer_sync();

    const float sc = 0.08838834764831845f * 1.4426950408889634f;

#pragma unroll 1
    for (int u = 0; u < 2; u++) {
        const int tile0 = kNumWqTiles + u * kTilesPerUnit;
        {
            uint32_t qf[8][2];
#pragma unroll
            for (int s = 0; s < 8; s++) {
                qf[s][0] = lds32(base + kOffQ + (uint32_t)((u * 128 + s * 16 + 2 * t) * 2));
                qf[s][1] = lds32(base + kOffQ + (uint32_t)((u * 128 + s * 16 + 8 + 2 * t) * 2));
            }
#pragma unroll 1
            for (int jj = 0; jj < 16; jj++) {
                const int j = 2 * jj + grp;
                const int i = tile0 + j;
                wait_full(i);
                const uint32_t tile = base + kOffRing + (i % kNSlot) * kTileBytes + k_row_off;
                float c0[4] = {0.f, 0.f, 0.f, 0.f}, c1[4] = {0.f, 0.f, 0.f, 0.f};
#pragma unroll
                for (int s = 0; s < 8; s++) {
                    uint32_t a0, a1, a2, a3;
                    const uint32_t chunk = (uint32_t)(2 * (s & 3) + (mi >> 1));
                    ldsm_x4(tile + (s >> 2) * 8192 + ((chunk ^ l8) << 4), a0, a1, a2, a3);
                    if (s & 1) mma16816(c1, a0, a1, a2, a3, qf[s][0], qf[s][1]);
                    else       mma16816(c0, a0, a1, a2, a3, qf[s][0], qf[s][1]);
                }
                release(i);
                if (t == 0) {
                    scores_s[j * 64 + wi * 16 + g] = c0[0] + c1[0];
                    scores_s[j * 64 + wi * 16 + g + 8] = c0[2] + c1[2];
                }
            }
        }
        consumer_sync();
        float inv_l;
        {
            float4 s0 = reinterpret_cast<const float4*>(scores_s)[tid * 2];
            float4 s1 = reinterpret_cast<const float4*>(scores_s)[tid * 2 + 1];
            float m = fmaxf(fmaxf(fmaxf(s0.x, s0.y), fmaxf(s0.z, s0.w)),
                            fmaxf(fmaxf(s1.x, s1.y), fmaxf(s1.z, s1.w)));
#pragma unroll
            for (int o = 16; o > 0; o >>= 1) m = fmaxf(m, __shfl_xor_sync(0xffffffffu, m, o));
            if (lane == 0) red_s[warp] = m;
            consumer_sync();
            m = red_s[0];
#pragma unroll
            for (int w = 1; w < 8; w++) m = fmaxf(m, red_s[w]);
            float p[8] = {s0.x, s0.y, s0.z, s0.w, s1.x, s1.y, s1.z, s1.w};
            float sum = 0.f;
            uint32_t hi[4], lo[4];
#pragma unroll
            for (int e = 0; e < 8; e++) {
                p[e] = exp2f((p[e] - m) * sc);
                sum += p[e];
            }
#pragma unroll
            for (int e = 0; e < 4; e++) {
                __nv_bfloat162 h2 = __floats2bfloat162_rn(p[2 * e], p[2 * e + 1]);
                float2 hf = __bfloat1622float2(h2);
                __nv_bfloat162 l2 = __floats2bfloat162_rn(p[2 * e] - hf.x, p[2 * e + 1] - hf.y);
                hi[e] = *reinterpret_cast<uint32_t*>(&h2);
                lo[e] = *reinterpret_cast<uint32_t*>(&l2);
            }
            reinterpret_cast<uint4*>(p_s)[tid] = make_uint4(hi[0], hi[1], hi[2], hi[3]);
            reinterpret_cast<uint4*>(p_s + 2048)[tid] = make_uint4(lo[0], lo[1], lo[2], lo[3]);
#pragma unroll
            for (int o = 16; o > 0; o >>= 1) sum += __shfl_xor_sync(0xffffffffu, sum, o);
            if (lane == 0) red_s[8 + warp] = sum;
            consumer_sync();
            float l = red_s[8];
#pragma unroll
            for (int w = 1; w < 8; w++) l += red_s[8 + w];
            inv_l = 1.0f / l;
        }
        {
            float oacc[8][4];
#pragma unroll
            for (int s = 0; s < 8; s++) { oacc[s][0] = oacc[s][1] = oacc[s][2] = oacc[s][3] = 0.f; }
            const uint32_t pb = base + kOffP + (uint32_t)((g & 1) * 4096 + (wi * 16 + 2 * t) * 2);
#pragma unroll 1
            for (int jj = 0; jj < 16; jj++) {
                const int j = 2 * jj + grp;
                const int i = tile0 + 32 + j;
                const uint32_t b0 = lds32(pb + j * 128);
                const uint32_t b1 = lds32(pb + j * 128 + 16);
                wait_full(i);
                const uint32_t tile = base + kOffRing + (i % kNSlot) * kTileBytes + v_row_off;
#pragma unroll
                for (int s = 0; s < 8; s++) {
                    uint32_t a0, a1, a2, a3;
                    const uint32_t chunk = (uint32_t)(2 * (s & 3) + (mi & 1));
                    ldsm_x4_t(tile + (s >> 2) * 8192 + ((chunk ^ l8) << 4), a0, a1, a2, a3);
                    mma16816(oacc[s], a0, a1, a2, a3, b0, b1);
                }
                release(i);
            }
#pragma unroll
            for (int s = 0; s < 8; s++) {
                if ((s >> 1) == t) {
                    ored_s[warp * 128 + s * 16 + g] = oacc[s][0] + oacc[s][1];
                    ored_s[warp * 128 + s * 16 + g + 8] = oacc[s][2] + oacc[s][3];
                }
            }
            consumer_sync();
            if (tid < 128) {
                float o = 0.f;
#pragma unroll
                for (int w = 0; w < 8; w++) o += ored_s[w * 128 + tid];
                o_s[u * 128 + tid] = __float2bfloat16(o * inv_l);
            }
        }
    }
    consumer_sync();

    {
        uint32_t of[8][2];
        const uint32_t ob = base + kOffO + (uint32_t)((g & 1) * 256 + t * 4);
#pragma unroll
        for (int s = 0; s < 8; s++) {
            of[s][0] = lds32(ob + s * 32);
            of[s][1] = lds32(ob + s * 32 + 16);
        }
        float* acc0 = g_acc + (prob * kB + 2 * bp) * kD;
#pragma unroll 1
        for (int cc = 0; cc < 5; cc++) {
            const int c = 2 * cc + grp;
            const int i = kNumWqTiles + 2 * kTilesPerUnit + c;
            wait_full(i);
            const uint32_t tile = base + kOffRing + (i % kNSlot) * kTileBytes + w_lane_off;
            float c0[4] = {0.f, 0.f, 0.f, 0.f}, c1[4] = {0.f, 0.f, 0.f, 0.f};
#pragma unroll
            for (int s = 0; s < 8; s++) {
                uint32_t a0, a1, a2, a3;
                ldsm_x4_t(tile + s * 2048, a0, a1, a2, a3);
                if (s & 1) mma16816(c1, a0, a1, a2, a3, of[s][0], of[s][1]);
                else       mma16816(c0, a0, a1, a2, a3, of[s][0], of[s][1]);
            }
            const int n = c * 64 + wi * 16 + g;
            float v = (t == 0) ? (c0[0] + c1[0]) : (t == 1) ? (c0[1] + c1[1]) : (t == 2) ? (c0[2] + c1[2]) : (c0[3] + c1[3]);
            atomicAdd(acc0 + (t & 1) * kD + n + (t >> 1) * 8, v);
        }
    }
    __threadfence();
    consumer_sync();
    if (tid == 0) {
        unsigned int old = atomicAdd(&g_count, 1u);
        *flag_s = (old == kNumCtas - 1) ? 1u : 0u;
    }
    consumer_sync();
    if (*flag_s) {
        __threadfence();
        for (int e = tid; e < 2 * kB * kD / 2; e += kConsumerThreads) {
            const int idx = 2 * e;
            const int pb2 = idx / kD, n = idx - pb2 * kD;
            float2 v = __ldcg(reinterpret_cast<const float2*>(g_acc + idx));
            __stcg(reinterpret_cast<float2*>(g_acc + idx), make_float2(0.f, 0.f));
            const int pr = pb2 >> 2, b = pb2 & 3;
            *reinterpret_cast<__nv_bfloat162*>(prm.out + b * (2 * kD) + pr * kD + n) =
                __floats2bfloat162_rn(v.x, v.y);
        }
        if (tid == 0) g_count = 0;
    }
}

typedef CUresult (*EncodeTiledFn)(CUtensorMap*, CUtensorMapDataType, cuuint32_t, void*, const cuuint64_t*,
                                  const cuuint64_t*, const cuuint32_t*, const cuuint32_t*, CUtensorMapInterleave,
                                  CUtensorMapSwizzle, CUtensorMapL2promotion, CUtensorMapFloatOOBfill);

void make_map(EncodeTiledFn fn, CUtensorMap* m, const void* ptr, uint64_t rows, uint64_t cols, uint32_t box_rows) {
    cuuint64_t dims[2] = {cols, rows};
    cuuint64_t strides[1] = {cols * 2};
    cuuint32_t box[2] = {64, box_rows};
    cuuint32_t es[2] = {1, 1};
    fn(m, CU_TENSOR_MAP_DATA_TYPE_BFLOAT16, 2, const_cast<void*>(ptr), dims, strides, box, es,
       CU_TENSOR_MAP_INTERLEAVE_NONE, CU_TENSOR_MAP_SWIZZLE_128B, CU_TENSOR_MAP_L2_PROMOTION_L2_256B,
       CU_TENSOR_MAP_FLOAT_OOB_FILL_NONE);
}

}

extern "C" void kernel_launch(void* const* d_in, const int* in_sizes, int n_in, void* d_out, int out_size) {
    (void)in_sizes; (void)n_in; (void)out_size;
    static EncodeTiledFn encode = nullptr;
    if (!encode) {
        void* fn = nullptr;
        cudaDriverEntryPointQueryResult qres;
        cudaGetDriverEntryPoint("cuTensorMapEncodeTiled", &fn, cudaEnableDefault, &qres);
        encode = (EncodeTiledFn)fn;
        cudaFuncSetAttribute(fused_decode_kernel, cudaFuncAttributeMaxDynamicSharedMemorySize, kSmemAlloc);
    }
    Params prm;
    for (int p = 0; p < 2; p++) {
        const void* x = d_in[5 * p + 0];
        const void* kc = d_in[5 * p + 1];
        const void* vc = d_in[5 * p + 2];
        const void* wq = d_in[5 * p + 3];
        const void* wo = d_in[5 * p + 4];
        prm.x[p] = (const __nv_bfloat16*)x;
        make_map(encode, &prm.k[p], kc, (uint64_t)kB * kH * kS, kDH, 64);
        make_map(encode, &prm.v[p], vc, (uint64_t)kB * kH * kS, kDH, 64);
        make_map(encode, &prm.wq[p], wq, kD, (uint64_t)kH * kDH, 128);
        make_map(encode, &prm.wo[p], wo, (uint64_t)kH * kDH, kD, 128);
    }
    prm.out = (__nv_bfloat16*)d_out;
    fused_decode_kernel<<<kNumCtas, kThreads, kSmemAlloc>>>(prm);
}
```

```cpp
#include <cuda_runtime.h>
#include <cuda_bf16.h>
#include <cuda.h>
#include <stdint.h>

namespace {

constexpr int kB = 4, kD = 640, kH = 32, kS = 8192, kDH = 128, kW = 2048;
#define NSLOT 6
#define WO_AT 40
constexpr int kNSlot = NSLOT;
static_assert(NSLOT % 2 == 0, "ring slots must be even");
constexpr int kTileBytes = 16384;
constexpr int kNumWqTiles = 5, kNumWoTiles = 5;
constexpr int kTilesPerUnit = 64;
constexpr int kNumTiles = kNumWqTiles + 2 * kTilesPerUnit;
constexpr int kConsumerThreads = 256;
constexpr int kThreads = kConsumerThreads + 32;
constexpr int kNumCtas = 128;
constexpr int kWoAt = WO_AT;

struct Params {
    CUtensorMap k[2], v[2], wq[2], wo[2];
    const __nv_bfloat16* x[2];
    __nv_bfloat16* out;
};

constexpr int kOffRing = 0;
constexpr int kOffWo = kNSlot * kTileBytes;
constexpr int kOffScores = kOffWo + kNumWoTiles * kTileBytes;
constexpr int kOffP = kOffScores + 2048 * 4;
constexpr int kOffORed = kOffP + 2 * 2048 * 2;
constexpr int kOffX = kOffORed + 8 * 128 * 4;
constexpr int kOffQPart = kOffX + 4 * 640 * 2;
constexpr int kOffQStage = kOffQPart + 4 * 64 * 4;
constexpr int kOffQ = kOffQStage + 4 * 64 * 2;
constexpr int kOffO = kOffQ + 2 * 128 * 2;
constexpr int kOffRed = kOffO + 4 * 128 * 2;
constexpr int kOffFlag = kOffRed + 16 * 4;
constexpr int kOffBar = kOffFlag + 16;
constexpr int kSmemBytes = kOffBar + (2 * kNSlot + 3) * 8;
constexpr int kSmemAlloc = kSmemBytes + 1024;
static_assert(kSmemAlloc <= 232448, "smem");

__device__ float g_acc[2 * kB * kD];
__device__ unsigned int g_count;

#define TL(k)
#define TLSM()

__device__ __forceinline__ uint32_t smem_u32(const void* p) {
    return (uint32_t)__cvta_generic_to_shared(p);
}
__device__ __forceinline__ void mbar_init(uint32_t bar, uint32_t count) {
    asm volatile("mbarrier.init.shared::cta.b64 [%0], %1;" ::"r"(bar), "r"(count) : "memory");
}
__device__ __forceinline__ void mbar_expect_tx(uint32_t bar, uint32_t bytes) {
    asm volatile("mbarrier.arrive.expect_tx.shared::cta.b64 _, [%0], %1;" ::"r"(bar), "r"(bytes) : "memory");
}
__device__ __forceinline__ void mbar_arrive(uint32_t bar) {
    asm volatile("mbarrier.arrive.shared::cta.b64 _, [%0];" ::"r"(bar) : "memory");
}
__device__ __forceinline__ bool mbar_try_wait(uint32_t bar, uint32_t parity) {
    uint32_t ok;
    asm volatile(
        "{\n\t.reg .pred p;\n\t"
        "mbarrier.try_wait.parity.shared::cta.b64 p, [%1], %2;\n\t"
        "selp.u32 %0, 1, 0, p;\n\t}"
        : "=r"(ok) : "r"(bar), "r"(parity) : "memory");
    return ok != 0;
}
__device__ __forceinline__ void mbar_wait(uint32_t bar, uint32_t parity) {
    uint32_t spins = 0;
    while (!mbar_try_wait(bar, parity)) {
        if (++spins > (1u << 24)) __trap();
    }
}
__device__ __forceinline__ void mbar_wait_cluster(uint32_t bar, uint32_t parity) {
    uint32_t spins = 0;
    while (true) {
        uint32_t ok;
        asm volatile(
            "{\n\t.reg .pred p;\n\t"
            "mbarrier.try_wait.parity.acquire.cluster.shared::cta.b64 p, [%1], %2;\n\t"
            "selp.u32 %0, 1, 0, p;\n\t}"
            : "=r"(ok) : "r"(bar), "r"(parity) : "memory");
        if (ok) break;
        if (++spins > (1u << 24)) __trap();
    }
}
__device__ __forceinline__ uint32_t mapa(uint32_t addr, uint32_t rank) {
    uint32_t r;
    asm volatile("mapa.shared::cluster.u32 %0, %1, %2;" : "=r"(r) : "r"(addr), "r"(rank));
    return r;
}
__device__ __forceinline__ void st_async_v4(uint32_t raddr, uint4 v, uint32_t rbar) {
    asm volatile("st.async.weak.shared::cluster.mbarrier::complete_tx::bytes.v4.b32 [%0], {%1,%2,%3,%4}, [%5];"
                 ::"r"(raddr), "r"(v.x), "r"(v.y), "r"(v.z), "r"(v.w), "r"(rbar) : "memory");
}
__device__ __forceinline__ void st_async_b32(uint32_t raddr, uint32_t v, uint32_t rbar) {
    asm volatile("st.async.weak.shared::cluster.mbarrier::complete_tx::bytes.b32 [%0], %1, [%2];"
                 ::"r"(raddr), "r"(v), "r"(rbar) : "memory");
}
__device__ __forceinline__ void tma_load_2d(uint32_t dst, const CUtensorMap* map, int c0, int c1,
                                            uint32_t bar, uint64_t policy) {
    asm volatile(
        "cp.async.bulk.tensor.2d.shared::cluster.global.mbarrier::complete_tx::bytes.L2::cache_hint "
        "[%0], [%1, {%3, %4}], [%2], %5;"
        ::"r"(dst), "l"(reinterpret_cast<uint64_t>(map)), "r"(bar), "r"(c0), "r"(c1), "l"(policy)
        : "memory");
}
__device__ __forceinline__ void ldsm_x4(uint32_t addr, uint32_t& r0, uint32_t& r1, uint32_t& r2, uint32_t& r3) {
    asm volatile("ldmatrix.sync.aligned.m8n8.x4.shared.b16 {%0,%1,%2,%3}, [%4];"
                 : "=r"(r0), "=r"(r1), "=r"(r2), "=r"(r3) : "r"(addr) : "memory");
}
__device__ __forceinline__ void ldsm_x4_t(uint32_t addr, uint32_t& r0, uint32_t& r1, uint32_t& r2, uint32_t& r3) {
    asm volatile("ldmatrix.sync.aligned.m8n8.x4.trans.shared.b16 {%0,%1,%2,%3}, [%4];"
                 : "=r"(r0), "=r"(r1), "=r"(r2), "=r"(r3) : "r"(addr) : "memory");
}
__device__ __forceinline__ void mma16816(float (&c)[4], uint32_t a0, uint32_t a1, uint32_t a2, uint32_t a3,
                                         uint32_t b0, uint32_t b1) {
    asm volatile(
        "mma.sync.aligned.m16n8k16.row.col.f32.bf16.bf16.f32 {%0,%1,%2,%3}, {%4,%5,%6,%7}, {%8,%9}, {%0,%1,%2,%3};"
        : "+f"(c[0]), "+f"(c[1]), "+f"(c[2]), "+f"(c[3])
        : "r"(a0), "r"(a1), "r"(a2), "r"(a3), "r"(b0), "r"(b1));
}
__device__ __forceinline__ void consumer_sync() {
    asm volatile("bar.sync 1, 256;" ::: "memory");
}
__device__ __forceinline__ uint32_t lds32(uint32_t addr) {
    uint32_t v;
    asm volatile("ld.shared.b32 %0, [%1];" : "=r"(v) : "r"(addr) : "memory");
    return v;
}

#define ORD 5
__device__ __forceinline__ int batch_of(int r, int u, int h, int prob) {
    return 2 * u + r;
}

__global__ void __cluster_dims__(2, 1, 1) __launch_bounds__(kThreads, 1)
fused_decode_kernel(const __grid_constant__ Params prm) {
    extern __shared__ unsigned char smem_raw[];
    const uint32_t raw = smem_u32(smem_raw);
    const uint32_t base = (raw + 1023u) & ~1023u;
    unsigned char* sm = smem_raw + (base - raw);

    const int tid = threadIdx.x;
    const int warp = tid >> 5, lane = tid & 31;
    const int blk = blockIdx.x;
    const int prob = blk >> 6;
    const int h = (blk & 63) >> 1;
    const int r = blk & 1;

    TL(0); TLSM();
    const uint32_t bar_full = base + kOffBar;
    const uint32_t bar_empty = bar_full + kNSlot * 8;
    const uint32_t bar_wo = bar_empty + kNSlot * 8;
    const uint32_t bar_xq = bar_wo + 8;
    const uint32_t bar_xo = bar_xq + 8;

    if (tid == 0) {
        for (int i = 0; i < kNSlot; i++) {
            mbar_init(bar_full + i * 8, 1);
            mbar_init(bar_empty + i * 8, 4);
        }
        mbar_init(bar_wo, 1);
        mbar_init(bar_xq, 1);
        mbar_init(bar_xo, 1);
        asm volatile("fence.mbarrier_init.release.cluster;" ::: "memory");
        asm volatile("fence.proxy.async.shared::cta;" ::: "memory");
        mbar_expect_tx(bar_xq, 2 * 64 * 2);
        mbar_expect_tx(bar_xo, 2 * 128 * 2);
    }
    __syncthreads();
    asm volatile("barrier.cluster.arrive.release.aligned;" ::: "memory");

    if (warp == 8) {
        if (lane == 0) {
            uint64_t pol_stream;
            asm volatile("createpolicy.fractional.L2::evict_first.b64 %0, 1.0;" : "=l"(pol_stream));
            const CUtensorMap* mk = &prm.k[prob];
            const CUtensorMap* mv = &prm.v[prob];
            const CUtensorMap* mq = &prm.wq[prob];
            const CUtensorMap* mo = &prm.wo[prob];
            for (int i = 0; i < kNumTiles; i++) {
                const int slot = i % kNSlot;
                const uint32_t full = bar_full + slot * 8;
                if (i >= kNSlot) mbar_wait(bar_empty + slot * 8, ((i / kNSlot) - 1) & 1);
                const uint32_t dst = base + kOffRing + slot * kTileBytes;
                mbar_expect_tx(full, kTileBytes);
                if (i < kNumWqTiles) {
                    tma_load_2d(dst, mq, h * kDH + r * 64, i * 128, full, pol_stream);
                } else {
                    const int rr = i - kNumWqTiles;
                    const int u = rr >> 6, j = rr & 63;
                    const int b = batch_of(r, u, h, prob);
#define ROT 0
                    const int rot = ROT == 0 ? 0 : ROT == 1 ? h : ROT == 2 ? blk * 5 : ROT == 3 ? 16 * r : ROT == 4 ? 16 * prob : (blk >> 2);
                    const int row = (b * kH + h) * kS + (kS - kW) + ((j + rot) & 31) * 64;
                    const CUtensorMap* m = (j < 32) ? mk : mv;
                    tma_load_2d(dst, m, 0, row, full, pol_stream);
                    tma_load_2d(dst + 8192, m, 64, row, full, pol_stream);
                }
                if (i == kWoAt) {
                    mbar_expect_tx(bar_wo, kNumWoTiles * kTileBytes);
                    for (int c = 0; c < kNumWoTiles; c++)
                        tma_load_2d(base + kOffWo + c * kTileBytes, mo, (r * kNumWoTiles + c) * 64, h * kDH, bar_wo,
                                    pol_stream);
                }
            }
        }
        return;
    }

    const int grp = warp >> 2, wi = warp & 3;
    const int g = lane >> 2, t = lane & 3;
    const int mi = lane >> 3, l8 = lane & 7;

    float* scores_s = reinterpret_cast<float*>(sm + kOffScores);
    __nv_bfloat16* p_s = reinterpret_cast<__nv_bfloat16*>(sm + kOffP);
    float* ored_s = reinterpret_cast<float*>(sm + kOffORed);
    float* qpart_s = reinterpret_cast<float*>(sm + kOffQPart);
    __nv_bfloat16* qstage_s = reinterpret_cast<__nv_bfloat16*>(sm + kOffQStage);
    float* red_s = reinterpret_cast<float*>(sm + kOffRed);
    volatile unsigned int* flag_s = reinterpret_cast<volatile unsigned int*>(sm + kOffFlag);

    for (int e = tid; e < 320; e += kConsumerThreads)
        reinterpret_cast<uint4*>(sm + kOffX)[e] = __ldg(reinterpret_cast<const uint4*>(prm.x[prob]) + e);
    consumer_sync();

    auto wait_full = [&](int i) { mbar_wait(bar_full + (i % kNSlot) * 8, (i / kNSlot) & 1); };
    auto release = [&](int i) {
        __syncwarp();
        if (lane == 0) mbar_arrive(bar_empty + (i % kNSlot) * 8);
    };

    const uint32_t w_row_off = (uint32_t)((l8 + ((mi >> 1) << 3)) * 128);
    const uint32_t k_row_off = (uint32_t)((16 * wi + l8 + ((mi & 1) << 3)) * 128);
    const uint32_t v_row_off = (uint32_t)((16 * wi + l8 + ((mi >> 1) << 3)) * 128);

    {
        float acc[4] = {0.f, 0.f, 0.f, 0.f};
        const uint32_t xb = base + kOffX + (uint32_t)((g & 3) * kD * 2 + t * 4);
        const uint32_t lane_off = w_row_off + (uint32_t)(((2 * wi + (mi & 1)) ^ l8) << 4);
#pragma unroll 1
        for (int i = grp; i < kNumWqTiles; i += 2) {
            wait_full(i);
            const uint32_t tile = base + kOffRing + (i % kNSlot) * kTileBytes + lane_off;
#pragma unroll
            for (int s = 0; s < 8; s++) {
                uint32_t a0, a1, a2, a3;
                ldsm_x4_t(tile + s * 2048, a0, a1, a2, a3);
                uint32_t b0 = lds32(xb + (i * 128 + s * 16) * 2);
                uint32_t b1 = lds32(xb + (i * 128 + s * 16 + 8) * 2);
                mma16816(acc, a0, a1, a2, a3, b0, b1);
            }
            release(i);
        }
        const int d = wi * 16 + g;
        if (grp == 1 && t < 2) {
            qpart_s[(2 * t) * 64 + d] = acc[0];
            qpart_s[(2 * t + 1) * 64 + d] = acc[1];
            qpart_s[(2 * t) * 64 + d + 8] = acc[2];
            qpart_s[(2 * t + 1) * 64 + d + 8] = acc[3];
        }
        consumer_sync();
        if (grp == 0 && t < 2) {
            qstage_s[(2 * t) * 64 + d] = __float2bfloat16(acc[0] + qpart_s[(2 * t) * 64 + d]);
            qstage_s[(2 * t + 1) * 64 + d] = __float2bfloat16(acc[1] + qpart_s[(2 * t + 1) * 64 + d]);
            qstage_s[(2 * t) * 64 + d + 8] = __float2bfloat16(acc[2] + qpart_s[(2 * t) * 64 + d + 8]);
            qstage_s[(2 * t + 1) * 64 + d + 8] = __float2bfloat16(acc[3] + qpart_s[(2 * t + 1) * 64 + d + 8]);
        }
        consumer_sync();
        asm volatile("barrier.cluster.wait.acquire.aligned;" ::: "memory");
        if (tid < 32) {
            const int uu = (tid >> 3) & 1, ch = tid & 7;
            const uint32_t qdst = base + kOffQ + (uint32_t)(uu * 256 + r * 128 + ch * 16);
            if (tid < 16) {
                uint4 v = *reinterpret_cast<const uint4*>(qstage_s + batch_of(r ^ 1, uu, h, prob) * 64 + ch * 8);
                st_async_v4(mapa(qdst, r ^ 1), v, mapa(bar_xq, r ^ 1));
            } else {
                uint4 v = *reinterpret_cast<const uint4*>(qstage_s + batch_of(r, uu, h, prob) * 64 + ch * 8);
                *reinterpret_cast<uint4*>(sm + kOffQ + uu * 256 + r * 128 + ch * 16) = v;
            }
        }
        consumer_sync();
        mbar_wait_cluster(bar_xq, 0);
    }
    TL(1);

    const float sc = 0.08838834764831845f * 1.4426950408889634f;

#pragma unroll 1
    for (int u = 0; u < 2; u++) {
        const int tile0 = kNumWqTiles + u * kTilesPerUnit;
        const int jpar = (grp ^ kNumWqTiles) & 1;
        {
            uint32_t qf[8][2];
#pragma unroll
            for (int s = 0; s < 8; s++) {
                qf[s][0] = lds32(base + kOffQ + (uint32_t)((u * 128 + s * 16 + 2 * t) * 2));
                qf[s][1] = lds32(base + kOffQ + (uint32_t)((u * 128 + s * 16 + 8 + 2 * t) * 2));
            }
#pragma unroll 1
            for (int jj = 0; jj < 16; jj++) {
                const int j = 2 * jj + jpar;
                const int i = tile0 + j;
                wait_full(i);
                const uint32_t tile = base + kOffRing + (i % kNSlot) * kTileBytes + k_row_off;
                float c0[4] = {0.f, 0.f, 0.f, 0.f}, c1[4] = {0.f, 0.f, 0.f, 0.f};
#pragma unroll
                for (int s = 0; s < 8; s++) {
                    uint32_t a0, a1, a2, a3;
                    const uint32_t chunk = (uint32_t)(2 * (s & 3) + (mi >> 1));
                    ldsm_x4(tile + (s >> 2) * 8192 + ((chunk ^ l8) << 4), a0, a1, a2, a3);
                    if (s & 1) mma16816(c1, a0, a1, a2, a3, qf[s][0], qf[s][1]);
                    else       mma16816(c0, a0, a1, a2, a3, qf[s][0], qf[s][1]);
                }
                release(i);
                if (t == 0) {
                    scores_s[j * 64 + wi * 16 + g] = c0[0] + c1[0];
                    scores_s[j * 64 + wi * 16 + g + 8] = c0[2] + c1[2];
                }
            }
        }
        consumer_sync();
        float inv_l;
        {
            float4 s0 = reinterpret_cast<const float4*>(scores_s)[tid * 2];
            float4 s1 = reinterpret_cast<const float4*>(scores_s)[tid * 2 + 1];
            float m = fmaxf(fmaxf(fmaxf(s0.x, s0.y), fmaxf(s0.z, s0.w)),
                            fmaxf(fmaxf(s1.x, s1.y), fmaxf(s1.z, s1.w)));
#pragma unroll
            for (int o = 16; o > 0; o >>= 1) m = fmaxf(m, __shfl_xor_sync(0xffffffffu, m, o));
            if (lane == 0) red_s[warp] = m;
            consumer_sync();
            m = red_s[0];
#pragma unroll
            for (int w = 1; w < 8; w++) m = fmaxf(m, red_s[w]);
            float p[8] = {s0.x, s0.y, s0.z, s0.w, s1.x, s1.y, s1.z, s1.w};
            float sum = 0.f;
            uint32_t hi[4], lo[4];
#pragma unroll
            for (int e = 0; e < 8; e++) {
                p[e] = exp2f((p[e] - m) * sc);
                sum += p[e];
            }
#pragma unroll
            for (int e = 0; e < 4; e++) {
                __nv_bfloat162 h2 = __floats2bfloat162_rn(p[2 * e], p[2 * e + 1]);
                float2 hf = __bfloat1622float2(h2);
                __nv_bfloat162 l2 = __floats2bfloat162_rn(p[2 * e] - hf.x, p[2 * e + 1] - hf.y);
                hi[e] = *reinterpret_cast<uint32_t*>(&h2);
                lo[e] = *reinterpret_cast<uint32_t*>(&l2);
            }
            reinterpret_cast<uint4*>(p_s)[tid] = make_uint4(hi[0], hi[1], hi[2], hi[3]);
            reinterpret_cast<uint4*>(p_s + 2048)[tid] = make_uint4(lo[0], lo[1], lo[2], lo[3]);
#pragma unroll
            for (int o = 16; o > 0; o >>= 1) sum += __shfl_xor_sync(0xffffffffu, sum, o);
            if (lane == 0) red_s[8 + warp] = sum;
            consumer_sync();
            float l = red_s[8];
#pragma unroll
            for (int w = 1; w < 8; w++) l += red_s[8 + w];
            inv_l = 1.0f / l;
        }
        {
            float oacc[8][4];
#pragma unroll
            for (int s = 0; s < 8; s++) { oacc[s][0] = oacc[s][1] = oacc[s][2] = oacc[s][3] = 0.f; }
            const uint32_t pb = base + kOffP + (uint32_t)((g & 1) * 4096 + (wi * 16 + 2 * t) * 2);
#pragma unroll 1
            for (int jj = 0; jj < 16; jj++) {
                const int j = 2 * jj + jpar;
                const int i = tile0 + 32 + j;
                const uint32_t b0 = lds32(pb + j * 128);
                const uint32_t b1 = lds32(pb + j * 128 + 16);
                wait_full(i);
                const uint32_t tile = base + kOffRing + (i % kNSlot) * kTileBytes + v_row_off;
#pragma unroll
                for (int s = 0; s < 8; s++) {
                    uint32_t a0, a1, a2, a3;
                    const uint32_t chunk = (uint32_t)(2 * (s & 3) + (mi & 1));
                    ldsm_x4_t(tile + (s >> 2) * 8192 + ((chunk ^ l8) << 4), a0, a1, a2, a3);
                    mma16816(oacc[s], a0, a1, a2, a3, b0, b1);
                }
                release(i);
            }
#pragma unroll
            for (int s = 0; s < 8; s++) {
                if ((s >> 1) == t) {
                    ored_s[warp * 128 + s * 16 + g] = oacc[s][0] + oacc[s][1];
                    ored_s[warp * 128 + s * 16 + g + 8] = oacc[s][2] + oacc[s][3];
                }
            }
            consumer_sync();
            if (tid < 128) {
                float o = 0.f;
#pragma unroll
                for (int w = 0; w < 8; w++) o += ored_s[w * 128 + tid];
                o *= inv_l;
                const float on = __shfl_down_sync(0xffffffffu, o, 1);
                if ((tid & 1) == 0) {
                    __nv_bfloat162 o2 = __floats2bfloat162_rn(o, on);
                    const uint32_t v = *reinterpret_cast<uint32_t*>(&o2);
                    const uint32_t off = (uint32_t)(kOffO + batch_of(r, u, h, prob) * 256 + tid * 2);
                    *reinterpret_cast<uint32_t*>(sm + off) = v;
                    st_async_b32(mapa(base + off, r ^ 1), v, mapa(bar_xo, r ^ 1));
                }
            }
            TL(2 + u);
        }
    }
    consumer_sync();
    mbar_wait_cluster(bar_xo, 0);
    mbar_wait(bar_wo, 0);

    {
        uint32_t of[8][2];
        const uint32_t ob = base + kOffO + (uint32_t)((g & 3) * 256 + t * 4);
#pragma unroll
        for (int s = 0; s < 8; s++) {
            of[s][0] = lds32(ob + s * 32);
            of[s][1] = lds32(ob + s * 32 + 16);
        }
        float* accp = g_acc + (prob * kB + 2 * (t & 1)) * kD + r * 320 + g + (t >> 1) * 8;
#pragma unroll 1
        for (int job = warp; job < 4 * kNumWoTiles; job += 8) {
            const int c = job >> 2, mt = job & 3;
            const uint32_t tile = base + kOffWo + c * kTileBytes + w_row_off + (uint32_t)(((2 * mt + (mi & 1)) ^ l8) << 4);
            float c0[4] = {0.f, 0.f, 0.f, 0.f}, c1[4] = {0.f, 0.f, 0.f, 0.f};
#pragma unroll
            for (int s = 0; s < 8; s++) {
                uint32_t a0, a1, a2, a3;
                ldsm_x4_t(tile + s * 2048, a0, a1, a2, a3);
                if (s & 1) mma16816(c1, a0, a1, a2, a3, of[s][0], of[s][1]);
                else       mma16816(c0, a0, a1, a2, a3, of[s][0], of[s][1]);
            }
            const float v0 = (t < 2) ? (c0[0] + c1[0]) : (c0[2] + c1[2]);
            const float v1 = (t < 2) ? (c0[1] + c1[1]) : (c0[3] + c1[3]);
            atomicAdd(accp + job * 16, v0);
            atomicAdd(accp + job * 16 + kD, v1);
        }
    }
    __threadfence();
    consumer_sync();
    if (tid == 0) {
        unsigned int old = atomicAdd(&g_count, 1u);
        *flag_s = (old == kNumCtas - 1) ? 1u : 0u;
    }
    consumer_sync();
    if (*flag_s) {
        __threadfence();
        float4 v[5];
#pragma unroll
        for (int k = 0; k < 5; k++) v[k] = __ldcg(reinterpret_cast<const float4*>(g_acc) + k * kConsumerThreads + tid);
#pragma unroll
        for (int k = 0; k < 5; k++) {
            const int idx = 4 * (k * kConsumerThreads + tid);
            const int pb2 = idx / kD, n = idx - pb2 * kD;
            const int pr = pb2 >> 2, b = pb2 & 3;
            __nv_bfloat162 lo2 = __floats2bfloat162_rn(v[k].x, v[k].y), hi2 = __floats2bfloat162_rn(v[k].z, v[k].w);
            uint2 o2 = make_uint2(*reinterpret_cast<uint32_t*>(&lo2), *reinterpret_cast<uint32_t*>(&hi2));
            *reinterpret_cast<uint2*>(prm.out + b * (2 * kD) + pr * kD + n) = o2;
            __stcg(reinterpret_cast<float4*>(g_acc) + k * kConsumerThreads + tid, make_float4(0.f, 0.f, 0.f, 0.f));
        }
        if (tid == 0) g_count = 0;
    }
    TL(4);
}

typedef CUresult (*EncodeTiledFn)(CUtensorMap*, CUtensorMapDataType, cuuint32_t, void*, const cuuint64_t*,
                                  const cuuint64_t*, const cuuint32_t*, const cuuint32_t*, CUtensorMapInterleave,
                                  CUtensorMapSwizzle, CUtensorMapL2promotion, CUtensorMapFloatOOBfill);

void make_map(EncodeTiledFn fn, CUtensorMap* m, const void* ptr, uint64_t rows, uint64_t cols, uint32_t box_rows) {
    cuuint64_t dims[2] = {cols, rows};
    cuuint64_t strides[1] = {cols * 2};
    cuuint32_t box[2] = {64, box_rows};
    cuuint32_t es[2] = {1, 1};
    fn(m, CU_TENSOR_MAP_DATA_TYPE_BFLOAT16, 2, const_cast<void*>(ptr), dims, strides, box, es,
       CU_TENSOR_MAP_INTERLEAVE_NONE, CU_TENSOR_MAP_SWIZZLE_128B, CU_TENSOR_MAP_L2_PROMOTION_L2_256B,
       CU_TENSOR_MAP_FLOAT_OOB_FILL_NONE);
}

}

extern "C" void kernel_launch(void* const* d_in, const int* in_sizes, int n_in, void* d_out, int out_size) {
    (void)in_sizes; (void)n_in; (void)out_size;
    static EncodeTiledFn encode = nullptr;
    if (!encode) {
        void* fn = nullptr;
        cudaDriverEntryPointQueryResult qres;
        cudaGetDriverEntryPoint("cuTensorMapEncodeTiled", &fn, cudaEnableDefault, &qres);
        encode = (EncodeTiledFn)fn;
        cudaFuncSetAttribute(fused_decode_kernel, cudaFuncAttributeMaxDynamicSharedMemorySize, kSmemAlloc);
    }
    Params prm;
    for (int p = 0; p < 2; p++) {
        const void* x = d_in[5 * p + 0];
        const void* kc = d_in[5 * p + 1];
        const void* vc = d_in[5 * p + 2];
        const void* wq = d_in[5 * p + 3];
        const void* wo = d_in[5 * p + 4];
        prm.x[p] = (const __nv_bfloat16*)x;
        make_map(encode, &prm.k[p], kc, (uint64_t)kB * kH * kS, kDH, 64);
        make_map(encode, &prm.v[p], vc, (uint64_t)kB * kH * kS, kDH, 64);
        make_map(encode, &prm.wq[p], wq, kD, (uint64_t)kH * kDH, 128);
        make_map(encode, &prm.wo[p], wo, (uint64_t)kH * kDH, kD, 128);
    }
    prm.out = (__nv_bfloat16*)d_out;
    fused_decode_kernel<<<kNumCtas, kThreads, kSmemAlloc>>>(prm);
}
```

```cpp
#include <cuda_runtime.h>
#include <cuda_bf16.h>
#include <cuda.h>
#include <stdint.h>

namespace {

constexpr int kB = 4, kD = 640, kH = 32, kS = 8192, kDH = 128, kW = 2048;
#define NSLOT 6
#define WO_AT 40
constexpr int kNSlot = NSLOT;
static_assert(NSLOT % 2 == 0, "ring slots must be even");
constexpr int kTileBytes = 16384;
constexpr int kNumWqTiles = 5, kNumWoTiles = 5;
constexpr int kTilesPerUnit = 64;
constexpr int kNumTiles = kNumWqTiles + 2 * kTilesPerUnit;
constexpr int kConsumerThreads = 256;
constexpr int kThreads = kConsumerThreads + 32;
constexpr int kNumCtas = 128;
constexpr int kWoAt = WO_AT;

struct Params {
    CUtensorMap k[2], v[2], wq[2], wo[2];
    const __nv_bfloat16* x[2];
    __nv_bfloat16* out;
};

constexpr int kOffRing = 0;
constexpr int kOffWo = kNSlot * kTileBytes;
#define WOC(c) (c)
constexpr int kOffScores = kOffWo + kNumWoTiles * kTileBytes;
constexpr int kOffP = kOffScores + 2048 * 4;
constexpr int kOffORed = kOffP + 2 * 2 * 2048 * 2;
constexpr int kOffX = kOffORed + 8 * 128 * 4;
constexpr int kOffQPart = kOffX + 4 * 640 * 2;
constexpr int kOffQStage = kOffQPart + 4 * 64 * 4;
constexpr int kOffQ = kOffQStage + 4 * 64 * 2;
constexpr int kOffO = kOffQ + 2 * 128 * 2;
constexpr int kOffRed = kOffO + 4 * 128 * 2;
constexpr int kOffFlag = kOffRed + 16 * 4;
constexpr int kOffBar = kOffFlag + 16;
constexpr int kSmemBytes = kOffBar + (2 * kNSlot + 3) * 8;
constexpr int kSmemAlloc = kSmemBytes + 1024;
static_assert(kSmemAlloc <= 232448, "smem");

__device__ float g_acc[2 * kB * kD];
__device__ unsigned int g_count;

#define TL(k)
#define TLSM()

__device__ __forceinline__ uint32_t smem_u32(const void* p) {
    return (uint32_t)__cvta_generic_to_shared(p);
}
__device__ __forceinline__ void mbar_init(uint32_t bar, uint32_t count) {
    asm volatile("mbarrier.init.shared::cta.b64 [%0], %1;" ::"r"(bar), "r"(count) : "memory");
}
__device__ __forceinline__ void mbar_expect_tx(uint32_t bar, uint32_t bytes) {
    asm volatile("mbarrier.arrive.expect_tx.shared::cta.b64 _, [%0], %1;" ::"r"(bar), "r"(bytes) : "memory");
}
__device__ __forceinline__ void mbar_arrive(uint32_t bar) {
    asm volatile("mbarrier.arrive.shared::cta.b64 _, [%0];" ::"r"(bar) : "memory");
}
__device__ __forceinline__ bool mbar_try_wait(uint32_t bar, uint32_t parity) {
    uint32_t ok;
    asm volatile(
        "{\n\t.reg .pred p;\n\t"
        "mbarrier.try_wait.parity.shared::cta.b64 p, [%1], %2;\n\t"
        "selp.u32 %0, 1, 0, p;\n\t}"
        : "=r"(ok) : "r"(bar), "r"(parity) : "memory");
    return ok != 0;
}
__device__ __forceinline__ void mbar_wait(uint32_t bar, uint32_t parity) {
    uint32_t spins = 0;
    while (!mbar_try_wait(bar, parity)) {
        if (++spins > (1u << 24)) __trap();
    }
}
__device__ __forceinline__ void mbar_wait_cluster(uint32_t bar, uint32_t parity) {
    uint32_t spins = 0;
    while (true) {
        uint32_t ok;
        asm volatile(
            "{\n\t.reg .pred p;\n\t"
            "mbarrier.try_wait.parity.acquire.cluster.shared::cta.b64 p, [%1], %2;\n\t"
            "selp.u32 %0, 1, 0, p;\n\t}"
            : "=r"(ok) : "r"(bar), "r"(parity) : "memory");
        if (ok) break;
        if (++spins > (1u << 24)) __trap();
    }
}
__device__ __forceinline__ uint32_t mapa(uint32_t addr, uint32_t rank) {
    uint32_t r;
    asm volatile("mapa.shared::cluster.u32 %0, %1, %2;" : "=r"(r) : "r"(addr), "r"(rank));
    return r;
}
__device__ __forceinline__ void st_async_v4(uint32_t raddr, uint4 v, uint32_t rbar) {
    asm volatile("st.async.weak.shared::cluster.mbarrier::complete_tx::bytes.v4.b32 [%0], {%1,%2,%3,%4}, [%5];"
                 ::"r"(raddr), "r"(v.x), "r"(v.y), "r"(v.z), "r"(v.w), "r"(rbar) : "memory");
}
__device__ __forceinline__ void st_async_b32(uint32_t raddr, uint32_t v, uint32_t rbar) {
    asm volatile("st.async.weak.shared::cluster.mbarrier::complete_tx::bytes.b32 [%0], %1, [%2];"
                 ::"r"(raddr), "r"(v), "r"(rbar) : "memory");
}
__device__ __forceinline__ void tma_load_2d(uint32_t dst, const CUtensorMap* map, int c0, int c1,
                                            uint32_t bar, uint64_t policy) {
    asm volatile(
        "cp.async.bulk.tensor.2d.shared::cluster.global.mbarrier::complete_tx::bytes.L2::cache_hint "
        "[%0], [%1, {%3, %4}], [%2], %5;"
        ::"r"(dst), "l"(reinterpret_cast<uint64_t>(map)), "r"(bar), "r"(c0), "r"(c1), "l"(policy)
        : "memory");
}
__device__ __forceinline__ void ldsm_x4(uint32_t addr, uint32_t& r0, uint32_t& r1, uint32_t& r2, uint32_t& r3) {
    asm volatile("ldmatrix.sync.aligned.m8n8.x4.shared.b16 {%0,%1,%2,%3}, [%4];"
                 : "=r"(r0), "=r"(r1), "=r"(r2), "=r"(r3) : "r"(addr) : "memory");
}
__device__ __forceinline__ void ldsm_x4_t(uint32_t addr, uint32_t& r0, uint32_t& r1, uint32_t& r2, uint32_t& r3) {
    asm volatile("ldmatrix.sync.aligned.m8n8.x4.trans.shared.b16 {%0,%1,%2,%3}, [%4];"
                 : "=r"(r0), "=r"(r1), "=r"(r2), "=r"(r3) : "r"(addr) : "memory");
}
__device__ __forceinline__ void mma16816(float (&c)[4], uint32_t a0, uint32_t a1, uint32_t a2, uint32_t a3,
                                         uint32_t b0, uint32_t b1) {
    asm volatile(
        "mma.sync.aligned.m16n8k16.row.col.f32.bf16.bf16.f32 {%0,%1,%2,%3}, {%4,%5,%6,%7}, {%8,%9}, {%0,%1,%2,%3};"
        : "+f"(c[0]), "+f"(c[1]), "+f"(c[2]), "+f"(c[3])
        : "r"(a0), "r"(a1), "r"(a2), "r"(a3), "r"(b0), "r"(b1));
}
__device__ __forceinline__ void consumer_sync() {
    asm volatile("bar.sync 1, 256;" ::: "memory");
}
__device__ __forceinline__ uint32_t lds32(uint32_t addr) {
    uint32_t v;
    asm volatile("ld.shared.b32 %0, [%1];" : "=r"(v) : "r"(addr) : "memory");
    return v;
}

#define ORD 5
__device__ __forceinline__ int batch_of(int r, int u, int h, int prob) {
    return 2 * u + r;
}

__global__ void __cluster_dims__(2, 1, 1) __launch_bounds__(kThreads, 1)
fused_decode_kernel(const __grid_constant__ Params prm) {
    extern __shared__ unsigned char smem_raw[];
    const uint32_t raw = smem_u32(smem_raw);
    const uint32_t base = (raw + 1023u) & ~1023u;
    unsigned char* sm = smem_raw + (base - raw);

    const int tid = threadIdx.x;
    const int warp = tid >> 5, lane = tid & 31;
    const int blk = blockIdx.x;
    const int prob = blk >> 6;
    const int h = (blk & 63) >> 1;
    const int r = blk & 1;

#define PH 0
    const bool kkvv = PH == 0 ? false : PH == 1 ? true : PH == 2 ? (h & 1) : PH == 3 ? (r != 0) : PH == 4 ? (prob != 0) : ((h >> 1) & 1);
    TL(0); TLSM();
    const uint32_t bar_full = base + kOffBar;
    const uint32_t bar_empty = bar_full + kNSlot * 8;
    const uint32_t bar_wo = bar_empty + kNSlot * 8;
    const uint32_t bar_xq = bar_wo + 8;
    const uint32_t bar_xo = bar_xq + 8;

    if (tid == 0) {
        for (int i = 0; i < kNSlot; i++) {
            mbar_init(bar_full + i * 8, 1);
            mbar_init(bar_empty + i * 8, 4);
        }
        mbar_init(bar_wo, 1);
        mbar_init(bar_xq, 1);
        mbar_init(bar_xo, 1);
        asm volatile("fence.mbarrier_init.release.cluster;" ::: "memory");
        asm volatile("fence.proxy.async.shared::cta;" ::: "memory");
        mbar_expect_tx(bar_xq, 2 * 64 * 2);
        mbar_expect_tx(bar_xo, 2 * 128 * 2);
    }
    __syncthreads();
    asm volatile("barrier.cluster.arrive.release.aligned;" ::: "memory");

    if (warp == 8) {
        if (lane == 0) {
            uint64_t pol_stream;
            asm volatile("createpolicy.fractional.L2::evict_first.b64 %0, 1.0;" : "=l"(pol_stream));
            const CUtensorMap* mk = &prm.k[prob];
            const CUtensorMap* mv = &prm.v[prob];
            const CUtensorMap* mq = &prm.wq[prob];
            const CUtensorMap* mo = &prm.wo[prob];
            for (int i = 0; i < kNumTiles; i++) {
                const int slot = i % kNSlot;
                const uint32_t full = bar_full + slot * 8;
                if (i >= kNSlot) mbar_wait(bar_empty + slot * 8, ((i / kNSlot) - 1) & 1);
                const uint32_t dst = base + kOffRing + slot * kTileBytes;
                mbar_expect_tx(full, kTileBytes);
                if (i < kNumWqTiles) {
                    tma_load_2d(dst, mq, h * kDH + r * 64, i * 128, full, pol_stream);
                } else {
                    const int rr = i - kNumWqTiles;
                    const int ph = rr >> 5, j = rr & 31;
                    const int isv = kkvv ? ph >> 1 : ph & 1;
                    const int u = kkvv ? ph & 1 : ph >> 1;
                    const int b = batch_of(r, u, h, prob);
                    const int row = (b * kH + h) * kS + (kS - kW) + j * 64;
                    const CUtensorMap* m = isv ? mv : mk;
                    tma_load_2d(dst, m, 0, row, full, pol_stream);
                    tma_load_2d(dst + 8192, m, 64, row, full, pol_stream);
                }
                if (i == kWoAt) {
                    mbar_expect_tx(bar_wo, kNumWoTiles * kTileBytes);
                    for (int c = 0; c < kNumWoTiles; c++)
                        tma_load_2d(base + kOffWo + WOC(c) * kTileBytes, mo, (r * kNumWoTiles + c) * 64, h * kDH, bar_wo,
                                    pol_stream);
                }
            }
        }
        return;
    }

    const int grp = warp >> 2, wi = warp & 3;
    const int g = lane >> 2, t = lane & 3;
    const int mi = lane >> 3, l8 = lane & 7;

    float* scores_s = reinterpret_cast<float*>(sm + kOffScores);
    __nv_bfloat16* p_s = reinterpret_cast<__nv_bfloat16*>(sm + kOffP);
    float* ored_s = reinterpret_cast<float*>(sm + kOffORed);
    float* qpart_s = reinterpret_cast<float*>(sm + kOffQPart);
    __nv_bfloat16* qstage_s = reinterpret_cast<__nv_bfloat16*>(sm + kOffQStage);
    float* red_s = reinterpret_cast<float*>(sm + kOffRed);
    volatile unsigned int* flag_s = reinterpret_cast<volatile unsigned int*>(sm + kOffFlag);

    for (int e = tid; e < 320; e += kConsumerThreads)
        reinterpret_cast<uint4*>(sm + kOffX)[e] = __ldg(reinterpret_cast<const uint4*>(prm.x[prob]) + e);
    consumer_sync();

    auto wait_full = [&](int i) { mbar_wait(bar_full + (i % kNSlot) * 8, (i / kNSlot) & 1); };
    auto release = [&](int i) {
        __syncwarp();
        if (lane == 0) mbar_arrive(bar_empty + (i % kNSlot) * 8);
    };

    const uint32_t w_row_off = (uint32_t)((l8 + ((mi >> 1) << 3)) * 128);
    const uint32_t k_row_off = (uint32_t)((16 * wi + l8 + ((mi & 1) << 3)) * 128);
    const uint32_t v_row_off = (uint32_t)((16 * wi + l8 + ((mi >> 1) << 3)) * 128);

    {
        float acc[4] = {0.f, 0.f, 0.f, 0.f};
        const uint32_t xb = base + kOffX + (uint32_t)((g & 3) * kD * 2 + t * 4);
        const uint32_t lane_off = w_row_off + (uint32_t)(((2 * wi + (mi & 1)) ^ l8) << 4);
#pragma unroll 1
        for (int i = grp; i < kNumWqTiles; i += 2) {
            wait_full(i);
            const uint32_t tile = base + kOffRing + (i % kNSlot) * kTileBytes + lane_off;
#pragma unroll
            for (int s = 0; s < 8; s++) {
                uint32_t a0, a1, a2, a3;
                ldsm_x4_t(tile + s * 2048, a0, a1, a2, a3);
                uint32_t b0 = lds32(xb + (i * 128 + s * 16) * 2);
                uint32_t b1 = lds32(xb + (i * 128 + s * 16 + 8) * 2);
                mma16816(acc, a0, a1, a2, a3, b0, b1);
            }
            release(i);
        }
        const int d = wi * 16 + g;
        if (grp == 1 && t < 2) {
            qpart_s[(2 * t) * 64 + d] = acc[0];
            qpart_s[(2 * t + 1) * 64 + d] = acc[1];
            qpart_s[(2 * t) * 64 + d + 8] = acc[2];
            qpart_s[(2 * t + 1) * 64 + d + 8] = acc[3];
        }
        consumer_sync();
        if (grp == 0 && t < 2) {
            qstage_s[(2 * t) * 64 + d] = __float2bfloat16(acc[0] + qpart_s[(2 * t) * 64 + d]);
            qstage_s[(2 * t + 1) * 64 + d] = __float2bfloat16(acc[1] + qpart_s[(2 * t + 1) * 64 + d]);
            qstage_s[(2 * t) * 64 + d + 8] = __float2bfloat16(acc[2] + qpart_s[(2 * t) * 64 + d + 8]);
            qstage_s[(2 * t + 1) * 64 + d + 8] = __float2bfloat16(acc[3] + qpart_s[(2 * t + 1) * 64 + d + 8]);
        }
        consumer_sync();
        asm volatile("barrier.cluster.wait.acquire.aligned;" ::: "memory");
        if (tid < 32) {
            const int uu = (tid >> 3) & 1, ch = tid & 7;
            const uint32_t qdst = base + kOffQ + (uint32_t)(uu * 256 + r * 128 + ch * 16);
            if (tid < 16) {
                uint4 v = *reinterpret_cast<const uint4*>(qstage_s + batch_of(r ^ 1, uu, h, prob) * 64 + ch * 8);
                st_async_v4(mapa(qdst, r ^ 1), v, mapa(bar_xq, r ^ 1));
            } else {
                uint4 v = *reinterpret_cast<const uint4*>(qstage_s + batch_of(r, uu, h, prob) * 64 + ch * 8);
                *reinterpret_cast<uint4*>(sm + kOffQ + uu * 256 + r * 128 + ch * 16) = v;
            }
        }
        consumer_sync();
        mbar_wait_cluster(bar_xq, 0);
    }
    TL(1);

    const float sc = 0.08838834764831845f * 1.4426950408889634f;

    float inv_l0 = 0.f, inv_l1 = 0.f;
#pragma unroll 1
    for (int ph = 0; ph < 4; ph++) {
        const int isv = kkvv ? ph >> 1 : ph & 1;
        const int u = kkvv ? ph & 1 : ph >> 1;
        const int tile0 = kNumWqTiles + ph * 32;
        const int jpar = (grp ^ kNumWqTiles) & 1;
        if (!isv) {
        {
            uint32_t qf[8][2];
#pragma unroll
            for (int s = 0; s < 8; s++) {
                qf[s][0] = lds32(base + kOffQ + (uint32_t)((u * 128 + s * 16 + 2 * t) * 2));
                qf[s][1] = lds32(base + kOffQ + (uint32_t)((u * 128 + s * 16 + 8 + 2 * t) * 2));
            }
#pragma unroll 1
            for (int jj = 0; jj < 16; jj++) {
                const int j = 2 * jj + jpar;
                const int i = tile0 + j;
                wait_full(i);
                const uint32_t tile = base + kOffRing + (i % kNSlot) * kTileBytes + k_row_off;
                float c0[4] = {0.f, 0.f, 0.f, 0.f}, c1[4] = {0.f, 0.f, 0.f, 0.f};
#pragma unroll
                for (int s = 0; s < 8; s++) {
                    uint32_t a0, a1, a2, a3;
                    const uint32_t chunk = (uint32_t)(2 * (s & 3) + (mi >> 1));
                    ldsm_x4(tile + (s >> 2) * 8192 + ((chunk ^ l8) << 4), a0, a1, a2, a3);
                    if (s & 1) mma16816(c1, a0, a1, a2, a3, qf[s][0], qf[s][1]);
                    else       mma16816(c0, a0, a1, a2, a3, qf[s][0], qf[s][1]);
                }
                release(i);
                if (t == 0) {
                    scores_s[j * 64 + wi * 16 + g] = c0[0] + c1[0];
                    scores_s[j * 64 + wi * 16 + g + 8] = c0[2] + c1[2];
                }
            }
        }
        consumer_sync();
        {
            float4 s0 = reinterpret_cast<const float4*>(scores_s)[tid * 2];
            float4 s1 = reinterpret_cast<const float4*>(scores_s)[tid * 2 + 1];
            float m = fmaxf(fmaxf(fmaxf(s0.x, s0.y), fmaxf(s0.z, s0.w)),
                            fmaxf(fmaxf(s1.x, s1.y), fmaxf(s1.z, s1.w)));
#pragma unroll
            for (int o = 16; o > 0; o >>= 1) m = fmaxf(m, __shfl_xor_sync(0xffffffffu, m, o));
            if (lane == 0) red_s[warp] = m;
            consumer_sync();
            m = red_s[0];
#pragma unroll
            for (int w = 1; w < 8; w++) m = fmaxf(m, red_s[w]);
            float p[8] = {s0.x, s0.y, s0.z, s0.w, s1.x, s1.y, s1.z, s1.w};
            float sum = 0.f;
            uint32_t hi[4], lo[4];
#pragma unroll
            for (int e = 0; e < 8; e++) {
                p[e] = exp2f((p[e] - m) * sc);
                sum += p[e];
            }
#pragma unroll
            for (int e = 0; e < 4; e++) {
                __nv_bfloat162 h2 = __floats2bfloat162_rn(p[2 * e], p[2 * e + 1]);
                float2 hf = __bfloat1622float2(h2);
                __nv_bfloat162 l2 = __floats2bfloat162_rn(p[2 * e] - hf.x, p[2 * e + 1] - hf.y);
                hi[e] = *reinterpret_cast<uint32_t*>(&h2);
                lo[e] = *reinterpret_cast<uint32_t*>(&l2);
            }
            reinterpret_cast<uint4*>(p_s + u * 4096)[tid] = make_uint4(hi[0], hi[1], hi[2], hi[3]);
            reinterpret_cast<uint4*>(p_s + u * 4096 + 2048)[tid] = make_uint4(lo[0], lo[1], lo[2], lo[3]);
#pragma unroll
            for (int o = 16; o > 0; o >>= 1) sum += __shfl_xor_sync(0xffffffffu, sum, o);
            if (lane == 0) red_s[8 + warp] = sum;
            consumer_sync();
            float l = red_s[8];
#pragma unroll
            for (int w = 1; w < 8; w++) l += red_s[8 + w];
            if (u) inv_l1 = 1.0f / l; else inv_l0 = 1.0f / l;
        }
        } else
        {
            const float inv_l = u ? inv_l1 : inv_l0;
            float oacc[8][4];
#pragma unroll
            for (int s = 0; s < 8; s++) { oacc[s][0] = oacc[s][1] = oacc[s][2] = oacc[s][3] = 0.f; }
            const uint32_t pb = base + kOffP + (uint32_t)(u * 8192 + (g & 1) * 4096 + (wi * 16 + 2 * t) * 2);
#pragma unroll 1
            for (int jj = 0; jj < 16; jj++) {
                const int j = 2 * jj + jpar;
                const int i = tile0 + j;
                const uint32_t b0 = lds32(pb + j * 128);
                const uint32_t b1 = lds32(pb + j * 128 + 16);
                wait_full(i);
                const uint32_t tile = base + kOffRing + (i % kNSlot) * kTileBytes + v_row_off;
#pragma unroll
                for (int s = 0; s < 8; s++) {
                    uint32_t a0, a1, a2, a3;
                    const uint32_t chunk = (uint32_t)(2 * (s & 3) + (mi & 1));
                    ldsm_x4_t(tile + (s >> 2) * 8192 + ((chunk ^ l8) << 4), a0, a1, a2, a3);
                    mma16816(oacc[s], a0, a1, a2, a3, b0, b1);
                }
                release(i);
            }
#pragma unroll
            for (int s = 0; s < 8; s++) {
                if ((s >> 1) == t) {
                    ored_s[warp * 128 + s * 16 + g] = oacc[s][0] + oacc[s][1];
                    ored_s[warp * 128 + s * 16 + g + 8] = oacc[s][2] + oacc[s][3];
                }
            }
            consumer_sync();
            if (tid < 128) {
                float o = 0.f;
#pragma unroll
                for (int w = 0; w < 8; w++) o += ored_s[w * 128 + tid];
                o *= inv_l;
                const float on = __shfl_down_sync(0xffffffffu, o, 1);
                if ((tid & 1) == 0) {
                    __nv_bfloat162 o2 = __floats2bfloat162_rn(o, on);
                    const uint32_t v = *reinterpret_cast<uint32_t*>(&o2);
                    const uint32_t off = (uint32_t)(kOffO + batch_of(r, u, h, prob) * 256 + tid * 2);
                    *reinterpret_cast<uint32_t*>(sm + off) = v;
                    st_async_b32(mapa(base + off, r ^ 1), v, mapa(bar_xo, r ^ 1));
                }
            }
            TL(2 + u);
        }
    }
    consumer_sync();
    mbar_wait_cluster(bar_xo, 0);
    mbar_wait(bar_wo, 0);

    {
        uint32_t of[8][2];
        const uint32_t ob = base + kOffO + (uint32_t)((g & 3) * 256 + t * 4);
#pragma unroll
        for (int s = 0; s < 8; s++) {
            of[s][0] = lds32(ob + s * 32);
            of[s][1] = lds32(ob + s * 32 + 16);
        }
        float* accp = g_acc + (prob * kB + 2 * (t & 1)) * kD + r * 320 + g + (t >> 1) * 8;
#pragma unroll 1
        for (int job = warp; job < 4 * kNumWoTiles; job += 8) {
            const int c = job >> 2, mt = job & 3;
            const uint32_t tile = base + kOffWo + WOC(c) * kTileBytes + w_row_off + (uint32_t)(((2 * mt + (mi & 1)) ^ l8) << 4);
            float c0[4] = {0.f, 0.f, 0.f, 0.f}, c1[4] = {0.f, 0.f, 0.f, 0.f};
#pragma unroll
            for (int s = 0; s < 8; s++) {
                uint32_t a0, a1, a2, a3;
                ldsm_x4_t(tile + s * 2048, a0, a1, a2, a3);
                if (s & 1) mma16816(c1, a0, a1, a2, a3, of[s][0], of[s][1]);
                else       mma16816(c0, a0, a1, a2, a3, of[s][0], of[s][1]);
            }
            const float v0 = (t < 2) ? (c0[0] + c1[0]) : (c0[2] + c1[2]);
            const float v1 = (t < 2) ? (c0[1] + c1[1]) : (c0[3] + c1[3]);
            atomicAdd(accp + job * 16, v0);
            atomicAdd(accp + job * 16 + kD, v1);
        }
    }
    __threadfence();
    consumer_sync();
    if (tid == 0) {
        unsigned int old = atomicAdd(&g_count, 1u);
        *flag_s = (old == kNumCtas - 1) ? 1u : 0u;
    }
    consumer_sync();
    if (*flag_s) {
        __threadfence();
        float4 v[5];
#pragma unroll
        for (int k = 0; k < 5; k++) v[k] = __ldcg(reinterpret_cast<const float4*>(g_acc) + k * kConsumerThreads + tid);
#pragma unroll
        for (int k = 0; k < 5; k++) {
            const int idx = 4 * (k * kConsumerThreads + tid);
            const int pb2 = idx / kD, n = idx - pb2 * kD;
            const int pr = pb2 >> 2, b = pb2 & 3;
            __nv_bfloat162 lo2 = __floats2bfloat162_rn(v[k].x, v[k].y), hi2 = __floats2bfloat162_rn(v[k].z, v[k].w);
            uint2 o2 = make_uint2(*reinterpret_cast<uint32_t*>(&lo2), *reinterpret_cast<uint32_t*>(&hi2));
            *reinterpret_cast<uint2*>(prm.out + b * (2 * kD) + pr * kD + n) = o2;
            __stcg(reinterpret_cast<float4*>(g_acc) + k * kConsumerThreads + tid, make_float4(0.f, 0.f, 0.f, 0.f));
        }
        if (tid == 0) g_count = 0;
    }
    TL(4);
}

typedef CUresult (*EncodeTiledFn)(CUtensorMap*, CUtensorMapDataType, cuuint32_t, void*, const cuuint64_t*,
                                  const cuuint64_t*, const cuuint32_t*, const cuuint32_t*, CUtensorMapInterleave,
                                  CUtensorMapSwizzle, CUtensorMapL2promotion, CUtensorMapFloatOOBfill);

void make_map(EncodeTiledFn fn, CUtensorMap* m, const void* ptr, uint64_t rows, uint64_t cols, uint32_t box_rows) {
    cuuint64_t dims[2] = {cols, rows};
    cuuint64_t strides[1] = {cols * 2};
    cuuint32_t box[2] = {64, box_rows};
    cuuint32_t es[2] = {1, 1};
    fn(m, CU_TENSOR_MAP_DATA_TYPE_BFLOAT16, 2, const_cast<void*>(ptr), dims, strides, box, es,
       CU_TENSOR_MAP_INTERLEAVE_NONE, CU_TENSOR_MAP_SWIZZLE_128B, CU_TENSOR_MAP_L2_PROMOTION_L2_256B,
       CU_TENSOR_MAP_FLOAT_OOB_FILL_NONE);
}

}

extern "C" void kernel_launch(void* const* d_in, const int* in_sizes, int n_in, void* d_out, int out_size) {
    (void)in_sizes; (void)n_in; (void)out_size;
    static EncodeTiledFn encode = nullptr;
    if (!encode) {
        void* fn = nullptr;
        cudaDriverEntryPointQueryResult qres;
        cudaGetDriverEntryPoint("cuTensorMapEncodeTiled", &fn, cudaEnableDefault, &qres);
        encode = (EncodeTiledFn)fn;
        cudaFuncSetAttribute(fused_decode_kernel, cudaFuncAttributeMaxDynamicSharedMemorySize, kSmemAlloc);
    }
    Params prm;
    for (int p = 0; p < 2; p++) {
        const void* x = d_in[5 * p + 0];
        const void* kc = d_in[5 * p + 1];
        const void* vc = d_in[5 * p + 2];
        const void* wq = d_in[5 * p + 3];
        const void* wo = d_in[5 * p + 4];
        prm.x[p] = (const __nv_bfloat16*)x;
        make_map(encode, &prm.k[p], kc, (uint64_t)kB * kH * kS, kDH, 64);
        make_map(encode, &prm.v[p], vc, (uint64_t)kB * kH * kS, kDH, 64);
        make_map(encode, &prm.wq[p], wq, kD, (uint64_t)kH * kDH, 128);
        make_map(encode, &prm.wo[p], wo, (uint64_t)kH * kDH, kD, 128);
    }
    prm.out = (__nv_bfloat16*)d_out;
    fused_decode_kernel<<<kNumCtas, kThreads, kSmemAlloc>>>(prm);
}
```

```cpp
#include <cuda_runtime.h>
#include <cuda_bf16.h>
#include <cuda.h>
#include <stdint.h>

namespace {

constexpr int kB = 4, kD = 640, kH = 32, kS = 8192, kDH = 128, kW = 2048;
#define NSLOT 6
#define WO_AT 110
constexpr int kNSlot = NSLOT;
static_assert(NSLOT % 2 == 0, "ring slots must be even");
constexpr int kTileBytes = 16384;
constexpr int kNumWqTiles = 5, kNumWoTiles = 5;
constexpr int kTilesPerUnit = 64;
constexpr int kNumTiles = kNumWqTiles + 2 * kTilesPerUnit;
constexpr int kConsumerThreads = 256;
constexpr int kThreads = kConsumerThreads + 32;
constexpr int kNumCtas = 128;
constexpr int kWoAt = WO_AT;

struct Params {
    CUtensorMap k[2], v[2], wq[2], wo[2];
    const __nv_bfloat16* x[2];
    __nv_bfloat16* out;
};

constexpr int kOffRing = 0;
constexpr int kOffWo = kNSlot * kTileBytes;
constexpr int kOffScores = kOffWo + kNumWoTiles * kTileBytes;
constexpr int kOffP = kOffScores + 2048 * 4;
constexpr int kOffORed = kOffP + 2 * 2 * 2048 * 2;
constexpr int kOffX = kOffORed + 8 * 128 * 4;
constexpr int kOffQPart = kOffX + 4 * 640 * 2;
constexpr int kOffQStage = kOffQPart + 4 * 64 * 4;
constexpr int kOffQ = kOffQStage + 4 * 64 * 2;
constexpr int kOffO = kOffQ + 2 * 128 * 2;
constexpr int kOffRed = kOffO + 4 * 128 * 2;
constexpr int kOffFlag = kOffRed + 16 * 4;
constexpr int kOffBar = kOffFlag + 16;
constexpr int kSmemBytes = kOffBar + (2 * kNSlot + 3) * 8;
constexpr int kSmemAlloc = kSmemBytes + 1024;
static_assert(kSmemAlloc <= 232448, "smem");

__device__ float g_acc[2 * kB * kD];
__device__ unsigned int g_count;

#define TL(k)
#define TLSM()

__device__ __forceinline__ uint32_t smem_u32(const void* p) {
    return (uint32_t)__cvta_generic_to_shared(p);
}
__device__ __forceinline__ void mbar_init(uint32_t bar, uint32_t count) {
    asm volatile("mbarrier.init.shared::cta.b64 [%0], %1;" ::"r"(bar), "r"(count) : "memory");
}
__device__ __forceinline__ void mbar_expect_tx(uint32_t bar, uint32_t bytes) {
    asm volatile("mbarrier.arrive.expect_tx.shared::cta.b64 _, [%0], %1;" ::"r"(bar), "r"(bytes) : "memory");
}
__device__ __forceinline__ void mbar_arrive(uint32_t bar) {
    asm volatile("mbarrier.arrive.shared::cta.b64 _, [%0];" ::"r"(bar) : "memory");
}
__device__ __forceinline__ bool mbar_try_wait(uint32_t bar, uint32_t parity) {
    uint32_t ok;
    asm volatile(
        "{\n\t.reg .pred p;\n\t"
        "mbarrier.try_wait.parity.shared::cta.b64 p, [%1], %2;\n\t"
        "selp.u32 %0, 1, 0, p;\n\t}"
        : "=r"(ok) : "r"(bar), "r"(parity) : "memory");
    return ok != 0;
}
__device__ __forceinline__ void mbar_wait(uint32_t bar, uint32_t parity) {
    uint32_t spins = 0;
    while (!mbar_try_wait(bar, parity)) {
        if (++spins > (1u << 24)) __trap();
    }
}
__device__ __forceinline__ void mbar_wait_cluster(uint32_t bar, uint32_t parity) {
    uint32_t spins = 0;
    while (true) {
        uint32_t ok;
        asm volatile(
            "{\n\t.reg .pred p;\n\t"
            "mbarrier.try_wait.parity.acquire.cluster.shared::cta.b64 p, [%1], %2;\n\t"
            "selp.u32 %0, 1, 0, p;\n\t}"
            : "=r"(ok) : "r"(bar), "r"(parity) : "memory");
        if (ok) break;
        if (++spins > (1u << 24)) __trap();
    }
}
__device__ __forceinline__ uint32_t mapa(uint32_t addr, uint32_t rank) {
    uint32_t r;
    asm volatile("mapa.shared::cluster.u32 %0, %1, %2;" : "=r"(r) : "r"(addr), "r"(rank));
    return r;
}
__device__ __forceinline__ void st_async_v4(uint32_t raddr, uint4 v, uint32_t rbar) {
    asm volatile("st.async.weak.shared::cluster.mbarrier::complete_tx::bytes.v4.b32 [%0], {%1,%2,%3,%4}, [%5];"
                 ::"r"(raddr), "r"(v.x), "r"(v.y), "r"(v.z), "r"(v.w), "r"(rbar) : "memory");
}
__device__ __forceinline__ void st_async_b32(uint32_t raddr, uint32_t v, uint32_t rbar) {
    asm volatile("st.async.weak.shared::cluster.mbarrier::complete_tx::bytes.b32 [%0], %1, [%2];"
                 ::"r"(raddr), "r"(v), "r"(rbar) : "memory");
}
__device__ __forceinline__ void tma_load_2d(uint32_t dst, const CUtensorMap* map, int c0, int c1,
                                            uint32_t bar, uint64_t policy) {
    asm volatile(
        "cp.async.bulk.tensor.2d.shared::cluster.global.mbarrier::complete_tx::bytes.L2::cache_hint "
        "[%0], [%1, {%3, %4}], [%2], %5;"
        ::"r"(dst), "l"(reinterpret_cast<uint64_t>(map)), "r"(bar), "r"(c0), "r"(c1), "l"(policy)
        : "memory");
}
__device__ __forceinline__ void ldsm_x4(uint32_t addr, uint32_t& r0, uint32_t& r1, uint32_t& r2, uint32_t& r3) {
    asm volatile("ldmatrix.sync.aligned.m8n8.x4.shared.b16 {%0,%1,%2,%3}, [%4];"
                 : "=r"(r0), "=r"(r1), "=r"(r2), "=r"(r3) : "r"(addr) : "memory");
}
__device__ __forceinline__ void ldsm_x4_t(uint32_t addr, uint32_t& r0, uint32_t& r1, uint32_t& r2, uint32_t& r3) {
    asm volatile("ldmatrix.sync.aligned.m8n8.x4.trans.shared.b16 {%0,%1,%2,%3}, [%4];"
                 : "=r"(r0), "=r"(r1), "=r"(r2), "=r"(r3) : "r"(addr) : "memory");
}
__device__ __forceinline__ void mma16816(float (&c)[4], uint32_t a0, uint32_t a1, uint32_t a2, uint32_t a3,
                                         uint32_t b0, uint32_t b1) {
    asm volatile(
        "mma.sync.aligned.m16n8k16.row.col.f32.bf16.bf16.f32 {%0,%1,%2,%3}, {%4,%5,%6,%7}, {%8,%9}, {%0,%1,%2,%3};"
        : "+f"(c[0]), "+f"(c[1]), "+f"(c[2]), "+f"(c[3])
        : "r"(a0), "r"(a1), "r"(a2), "r"(a3), "r"(b0), "r"(b1));
}
__device__ __forceinline__ void consumer_sync() {
    asm volatile("bar.sync 1, 256;" ::: "memory");
}
__device__ __forceinline__ uint32_t lds32(uint32_t addr) {
    uint32_t v;
    asm volatile("ld.shared.b32 %0, [%1];" : "=r"(v) : "r"(addr) : "memory");
    return v;
}

__device__ __forceinline__ int batch_of(int r, int u, int h) { return (2 * u + r + h) & 3; }

__global__ void __cluster_dims__(2, 1, 1) __launch_bounds__(kThreads, 1)
fused_decode_kernel(const __grid_constant__ Params prm) {
    extern __shared__ unsigned char smem_raw[];
    const uint32_t raw = smem_u32(smem_raw);
    const uint32_t base = (raw + 1023u) & ~1023u;
    unsigned char* sm = smem_raw + (base - raw);

    const int tid = threadIdx.x;
    const int warp = tid >> 5, lane = tid & 31;
    const int blk = blockIdx.x;
    const int prob = blk >> 6;
    const int h = (blk & 63) >> 1;
    const int r = blk & 1;

    TL(0); TLSM();
    const uint32_t bar_full = base + kOffBar;
    const uint32_t bar_empty = bar_full + kNSlot * 8;
    const uint32_t bar_wo = bar_empty + kNSlot * 8;
    const uint32_t bar_xq = bar_wo + 8;
    const uint32_t bar_xo = bar_xq + 8;

    if (tid == 0) {
        for (int i = 0; i < kNSlot; i++) {
            mbar_init(bar_full + i * 8, 1);
            mbar_init(bar_empty + i * 8, 4);
        }
        mbar_init(bar_wo, 1);
        mbar_init(bar_xq, 1);
        mbar_init(bar_xo, 1);
        asm volatile("fence.mbarrier_init.release.cluster;" ::: "memory");
        asm volatile("fence.proxy.async.shared::cta;" ::: "memory");
        mbar_expect_tx(bar_xq, 2 * 64 * 2);
        mbar_expect_tx(bar_xo, 2 * 128 * 2);
    }
    __syncthreads();
    asm volatile("barrier.cluster.arrive.release.aligned;" ::: "memory");

    if (warp == 8) {
        if (lane == 0) {
            uint64_t pol_stream;
            asm volatile("createpolicy.fractional.L2::evict_first.b64 %0, 1.0;" : "=l"(pol_stream));
            const CUtensorMap* mk = &prm.k[prob];
            const CUtensorMap* mv = &prm.v[prob];
            const CUtensorMap* mq = &prm.wq[prob];
            const CUtensorMap* mo = &prm.wo[prob];
            for (int i = 0; i < kNumTiles; i++) {
                const int slot = i % kNSlot;
                const uint32_t full = bar_full + slot * 8;
                if (i >= kNSlot) mbar_wait(bar_empty + slot * 8, ((i / kNSlot) - 1) & 1);
                const uint32_t dst = base + kOffRing + slot * kTileBytes;
                mbar_expect_tx(full, kTileBytes);
                if (i < kNumWqTiles) {
                    tma_load_2d(dst, mq, h * kDH + r * 64, i * 128, full, pol_stream);
                } else {
                    const int rr = i - kNumWqTiles;
                    const int ph = rr >> 5, j = rr & 31;
                    const int isv = ph >> 1, u = ph & 1;
                    const int b = batch_of(r, u, h);
                    const int row = (b * kH + h) * kS + (kS - kW) + j * 64;
                    const CUtensorMap* m = isv ? mv : mk;
                    tma_load_2d(dst, m, 0, row, full, pol_stream);
                    tma_load_2d(dst + 8192, m, 64, row, full, pol_stream);
                }
                if (i == kWoAt) {
                    mbar_expect_tx(bar_wo, kNumWoTiles * kTileBytes);
                    for (int c = 0; c < kNumWoTiles; c++)
                        tma_load_2d(base + kOffWo + c * kTileBytes, mo, (r * kNumWoTiles + c) * 64, h * kDH, bar_wo,
                                    pol_stream);
                }
            }
        }
        return;
    }

    const int grp = warp >> 2, wi = warp & 3;
    const int g = lane >> 2, t = lane & 3;
    const int mi = lane >> 3, l8 = lane & 7;

    float* scores_s = reinterpret_cast<float*>(sm + kOffScores);
    __nv_bfloat16* p_s = reinterpret_cast<__nv_bfloat16*>(sm + kOffP);
    float* ored_s = reinterpret_cast<float*>(sm + kOffORed);
    float* qpart_s = reinterpret_cast<float*>(sm + kOffQPart);
    __nv_bfloat16* qstage_s = reinterpret_cast<__nv_bfloat16*>(sm + kOffQStage);
    float* red_s = reinterpret_cast<float*>(sm + kOffRed);
    volatile unsigned int* flag_s = reinterpret_cast<volatile unsigned int*>(sm + kOffFlag);

    for (int e = tid; e < 320; e += kConsumerThreads)
        reinterpret_cast<uint4*>(sm + kOffX)[e] = __ldg(reinterpret_cast<const uint4*>(prm.x[prob]) + e);
    consumer_sync();

    auto wait_full = [&](int i) { mbar_wait(bar_full + (i % kNSlot) * 8, (i / kNSlot) & 1); };
    auto release = [&](int i) {
        __syncwarp();
        if (lane == 0) mbar_arrive(bar_empty + (i % kNSlot) * 8);
    };

    const uint32_t w_row_off = (uint32_t)((l8 + ((mi >> 1) << 3)) * 128);
    const uint32_t k_row_off = (uint32_t)((16 * wi + l8 + ((mi & 1) << 3)) * 128);
    const uint32_t v_row_off = (uint32_t)((16 * wi + l8 + ((mi >> 1) << 3)) * 128);

    {
        float acc[4] = {0.f, 0.f, 0.f, 0.f};
        const uint32_t xb = base + kOffX + (uint32_t)((g & 3) * kD * 2 + t * 4);
        const uint32_t lane_off = w_row_off + (uint32_t)(((2 * wi + (mi & 1)) ^ l8) << 4);
#pragma unroll 1
        for (int i = grp; i < kNumWqTiles; i += 2) {
            wait_full(i);
            const uint32_t tile = base + kOffRing + (i % kNSlot) * kTileBytes + lane_off;
#pragma unroll
            for (int s = 0; s < 8; s++) {
                uint32_t a0, a1, a2, a3;
                ldsm_x4_t(tile + s * 2048, a0, a1, a2, a3);
                uint32_t b0 = lds32(xb + (i * 128 + s * 16) * 2);
                uint32_t b1 = lds32(xb + (i * 128 + s * 16 + 8) * 2);
                mma16816(acc, a0, a1, a2, a3, b0, b1);
            }
            release(i);
        }
        const int d = wi * 16 + g;
        if (grp == 1 && t < 2) {
            qpart_s[(2 * t) * 64 + d] = acc[0];
            qpart_s[(2 * t + 1) * 64 + d] = acc[1];
            qpart_s[(2 * t) * 64 + d + 8] = acc[2];
            qpart_s[(2 * t + 1) * 64 + d + 8] = acc[3];
        }
        consumer_sync();
        if (grp == 0 && t < 2) {
            qstage_s[(2 * t) * 64 + d] = __float2bfloat16(acc[0] + qpart_s[(2 * t) * 64 + d]);
            qstage_s[(2 * t + 1) * 64 + d] = __float2bfloat16(acc[1] + qpart_s[(2 * t + 1) * 64 + d]);
            qstage_s[(2 * t) * 64 + d + 8] = __float2bfloat16(acc[2] + qpart_s[(2 * t) * 64 + d + 8]);
            qstage_s[(2 * t + 1) * 64 + d + 8] = __float2bfloat16(acc[3] + qpart_s[(2 * t + 1) * 64 + d + 8]);
        }
        consumer_sync();
        asm volatile("barrier.cluster.wait.acquire.aligned;" ::: "memory");
        if (tid < 32) {
            const int uu = (tid >> 3) & 1, ch = tid & 7;
            const uint32_t qdst = base + kOffQ + (uint32_t)(uu * 256 + r * 128 + ch * 16);
            if (tid < 16) {
                uint4 v = *reinterpret_cast<const uint4*>(qstage_s + batch_of(r ^ 1, uu, h) * 64 + ch * 8);
                st_async_v4(mapa(qdst, r ^ 1), v, mapa(bar_xq, r ^ 1));
            } else {
                uint4 v = *reinterpret_cast<const uint4*>(qstage_s + batch_of(r, uu, h) * 64 + ch * 8);
                *reinterpret_cast<uint4*>(sm + kOffQ + uu * 256 + r * 128 + ch * 16) = v;
            }
        }
        consumer_sync();
        mbar_wait_cluster(bar_xq, 0);
    }
    TL(1);

    const float sc = 0.08838834764831845f * 1.4426950408889634f;

    float inv_l0 = 0.f, inv_l1 = 0.f;
#pragma unroll 1
    for (int ph = 0; ph < 4; ph++) {
        const int isv = ph >> 1, u = ph & 1;
        const int tile0 = kNumWqTiles + ph * 32;
        const int jpar = (grp ^ kNumWqTiles) & 1;
        if (!isv) {
        {
            uint32_t qf[8][2];
#pragma unroll
            for (int s = 0; s < 8; s++) {
                qf[s][0] = lds32(base + kOffQ + (uint32_t)((u * 128 + s * 16 + 2 * t) * 2));
                qf[s][1] = lds32(base + kOffQ + (uint32_t)((u * 128 + s * 16 + 8 + 2 * t) * 2));
            }
#pragma unroll 1
            for (int jj = 0; jj < 16; jj++) {
                const int j = 2 * jj + jpar;
                const int i = tile0 + j;
                wait_full(i);
                const uint32_t tile = base + kOffRing + (i % kNSlot) * kTileBytes + k_row_off;
                float c0[4] = {0.f, 0.f, 0.f, 0.f}, c1[4] = {0.f, 0.f, 0.f, 0.f};
#pragma unroll
                for (int s = 0; s < 8; s++) {
                    uint32_t a0, a1, a2, a3;
                    const uint32_t chunk = (uint32_t)(2 * (s & 3) + (mi >> 1));
                    ldsm_x4(tile + (s >> 2) * 8192 + ((chunk ^ l8) << 4), a0, a1, a2, a3);
                    if (s & 1) mma16816(c1, a0, a1, a2, a3, qf[s][0], qf[s][1]);
                    else       mma16816(c0, a0, a1, a2, a3, qf[s][0], qf[s][1]);
                }
                release(i);
                if (t == 0) {
                    scores_s[j * 64 + wi * 16 + g] = c0[0] + c1[0];
                    scores_s[j * 64 + wi * 16 + g + 8] = c0[2] + c1[2];
                }
            }
        }
        consumer_sync();
        {
            float4 s0 = reinterpret_cast<const float4*>(scores_s)[tid * 2];
            float4 s1 = reinterpret_cast<const float4*>(scores_s)[tid * 2 + 1];
            float m = fmaxf(fmaxf(fmaxf(s0.x, s0.y), fmaxf(s0.z, s0.w)),
                            fmaxf(fmaxf(s1.x, s1.y), fmaxf(s1.z, s1.w)));
#pragma unroll
            for (int o = 16; o > 0; o >>= 1) m = fmaxf(m, __shfl_xor_sync(0xffffffffu, m, o));
            if (lane == 0) red_s[warp] = m;
            consumer_sync();
            m = red_s[0];
#pragma unroll
            for (int w = 1; w < 8; w++) m = fmaxf(m, red_s[w]);
            float p[8] = {s0.x, s0.y, s0.z, s0.w, s1.x, s1.y, s1.z, s1.w};
            float sum = 0.f;
            uint32_t hi[4], lo[4];
#pragma unroll
            for (int e = 0; e < 8; e++) {
                p[e] = exp2f((p[e] - m) * sc);
                sum += p[e];
            }
#pragma unroll
            for (int e = 0; e < 4; e++) {
                __nv_bfloat162 h2 = __floats2bfloat162_rn(p[2 * e], p[2 * e + 1]);
                float2 hf = __bfloat1622float2(h2);
                __nv_bfloat162 l2 = __floats2bfloat162_rn(p[2 * e] - hf.x, p[2 * e + 1] - hf.y);
                hi[e] = *reinterpret_cast<uint32_t*>(&h2);
                lo[e] = *reinterpret_cast<uint32_t*>(&l2);
            }
            reinterpret_cast<uint4*>(p_s + u * 4096)[tid] = make_uint4(hi[0], hi[1], hi[2], hi[3]);
            reinterpret_cast<uint4*>(p_s + u * 4096 + 2048)[tid] = make_uint4(lo[0], lo[1], lo[2], lo[3]);
#pragma unroll
            for (int o = 16; o > 0; o >>= 1) sum += __shfl_xor_sync(0xffffffffu, sum, o);
            if (lane == 0) red_s[8 + warp] = sum;
            consumer_sync();
            float l = red_s[8];
#pragma unroll
            for (int w = 1; w < 8; w++) l += red_s[8 + w];
            if (u) inv_l1 = 1.0f / l; else inv_l0 = 1.0f / l;
        }
        } else
        {
            const float inv_l = u ? inv_l1 : inv_l0;
            float oacc[8][4];
#pragma unroll
            for (int s = 0; s < 8; s++) { oacc[s][0] = oacc[s][1] = oacc[s][2] = oacc[s][3] = 0.f; }
            const uint32_t pb = base + kOffP + (uint32_t)(u * 8192 + (g & 1) * 4096 + (wi * 16 + 2 * t) * 2);
#pragma unroll 1
            for (int jj = 0; jj < 16; jj++) {
                const int j = 2 * jj + jpar;
                const int i = tile0 + j;
                const uint32_t b0 = lds32(pb + j * 128);
                const uint32_t b1 = lds32(pb + j * 128 + 16);
                wait_full(i);
                const uint32_t tile = base + kOffRing + (i % kNSlot) * kTileBytes + v_row_off;
#pragma unroll
                for (int s = 0; s < 8; s++) {
                    uint32_t a0, a1, a2, a3;
                    const uint32_t chunk = (uint32_t)(2 * (s & 3) + (mi & 1));
                    ldsm_x4_t(tile + (s >> 2) * 8192 + ((chunk ^ l8) << 4), a0, a1, a2, a3);
                    mma16816(oacc[s], a0, a1, a2, a3, b0, b1);
                }
                release(i);
            }
#pragma unroll
            for (int s = 0; s < 8; s++) {
                if ((s >> 1) == t) {
                    ored_s[warp * 128 + s * 16 + g] = oacc[s][0] + oacc[s][1];
                    ored_s[warp * 128 + s * 16 + g + 8] = oacc[s][2] + oacc[s][3];
                }
            }
            consumer_sync();
            if (tid < 128) {
                float o = 0.f;
#pragma unroll
                for (int w = 0; w < 8; w++) o += ored_s[w * 128 + tid];
                o *= inv_l;
                const float on = __shfl_down_sync(0xffffffffu, o, 1);
                if ((tid & 1) == 0) {
                    __nv_bfloat162 o2 = __floats2bfloat162_rn(o, on);
                    const uint32_t v = *reinterpret_cast<uint32_t*>(&o2);
                    const uint32_t off = (uint32_t)(kOffO + batch_of(r, u, h) * 256 + tid * 2);
                    *reinterpret_cast<uint32_t*>(sm + off) = v;
                    st_async_b32(mapa(base + off, r ^ 1), v, mapa(bar_xo, r ^ 1));
                }
            }
            TL(2 + u);
        }
    }
    consumer_sync();
    mbar_wait_cluster(bar_xo, 0);
    mbar_wait(bar_wo, 0);

    {
        uint32_t of[8][2];
        const uint32_t ob = base + kOffO + (uint32_t)((g & 3) * 256 + t * 4);
#pragma unroll
        for (int s = 0; s < 8; s++) {
            of[s][0] = lds32(ob + s * 32);
            of[s][1] = lds32(ob + s * 32 + 16);
        }
        float* accp = g_acc + (prob * kB + 2 * (t & 1)) * kD + r * 320 + g + (t >> 1) * 8;
#pragma unroll 1
        for (int job = warp; job < 4 * kNumWoTiles; job += 8) {
            const int c = job >> 2, mt = job & 3;
            const uint32_t tile = base + kOffWo + c * kTileBytes + w_row_off + (uint32_t)(((2 * mt + (mi & 1)) ^ l8) << 4);
            float c0[4] = {0.f, 0.f, 0.f, 0.f}, c1[4] = {0.f, 0.f, 0.f, 0.f};
#pragma unroll
            for (int s = 0; s < 8; s++) {
                uint32_t a0, a1, a2, a3;
                ldsm_x4_t(tile + s * 2048, a0, a1, a2, a3);
                if (s & 1) mma16816(c1, a0, a1, a2, a3, of[s][0], of[s][1]);
                else       mma16816(c0, a0, a1, a2, a3, of[s][0], of[s][1]);
            }
            const float v0 = (t < 2) ? (c0[0] + c1[0]) : (c0[2] + c1[2]);
            const float v1 = (t < 2) ? (c0[1] + c1[1]) : (c0[3] + c1[3]);
            atomicAdd(accp + job * 16, v0);
            atomicAdd(accp + job * 16 + kD, v1);
        }
    }
    __threadfence();
    consumer_sync();
    if (tid == 0) {
        unsigned int old = atomicAdd(&g_count, 1u);
        *flag_s = (old == kNumCtas - 1) ? 1u : 0u;
    }
    consumer_sync();
    if (*flag_s) {
        __threadfence();
        float4 v[5];
#pragma unroll
        for (int k = 0; k < 5; k++) v[k] = __ldcg(reinterpret_cast<const float4*>(g_acc) + k * kConsumerThreads + tid);
#pragma unroll
        for (int k = 0; k < 5; k++) {
            const int idx = 4 * (k * kConsumerThreads + tid);
            const int pb2 = idx / kD, n = idx - pb2 * kD;
            const int pr = pb2 >> 2, b = pb2 & 3;
            __nv_bfloat162 lo2 = __floats2bfloat162_rn(v[k].x, v[k].y), hi2 = __floats2bfloat162_rn(v[k].z, v[k].w);
            uint2 o2 = make_uint2(*reinterpret_cast<uint32_t*>(&lo2), *reinterpret_cast<uint32_t*>(&hi2));
            *reinterpret_cast<uint2*>(prm.out + b * (2 * kD) + pr * kD + n) = o2;
            __stcg(reinterpret_cast<float4*>(g_acc) + k * kConsumerThreads + tid, make_float4(0.f, 0.f, 0.f, 0.f));
        }
        if (tid == 0) g_count = 0;
    }
    TL(4);
}

typedef CUresult (*EncodeTiledFn)(CUtensorMap*, CUtensorMapDataType, cuuint32_t, void*, const cuuint64_t*,
                                  const cuuint64_t*, const cuuint32_t*, const cuuint32_t*, CUtensorMapInterleave,
                                  CUtensorMapSwizzle, CUtensorMapL2promotion, CUtensorMapFloatOOBfill);

void make_map(EncodeTiledFn fn, CUtensorMap* m, const void* ptr, uint64_t rows, uint64_t cols, uint32_t box_rows) {
    cuuint64_t dims[2] = {cols, rows};
    cuuint64_t strides[1] = {cols * 2};
    cuuint32_t box[2] = {64, box_rows};
    cuuint32_t es[2] = {1, 1};
    fn(m, CU_TENSOR_MAP_DATA_TYPE_BFLOAT16, 2, const_cast<void*>(ptr), dims, strides, box, es,
       CU_TENSOR_MAP_INTERLEAVE_NONE, CU_TENSOR_MAP_SWIZZLE_128B, CU_TENSOR_MAP_L2_PROMOTION_L2_256B,
       CU_TENSOR_MAP_FLOAT_OOB_FILL_NONE);
}

}

extern "C" void kernel_launch(void* const* d_in, const int* in_sizes, int n_in, void* d_out, int out_size) {
    (void)in_sizes; (void)n_in; (void)out_size;
    static EncodeTiledFn encode = nullptr;
    if (!encode) {
        void* fn = nullptr;
        cudaDriverEntryPointQueryResult qres;
        cudaGetDriverEntryPoint("cuTensorMapEncodeTiled", &fn, cudaEnableDefault, &qres);
        encode = (EncodeTiledFn)fn;
        cudaFuncSetAttribute(fused_decode_kernel, cudaFuncAttributeMaxDynamicSharedMemorySize, kSmemAlloc);
    }
    Params prm;
    for (int p = 0; p < 2; p++) {
        const void* x = d_in[5 * p + 0];
        const void* kc = d_in[5 * p + 1];
        const void* vc = d_in[5 * p + 2];
        const void* wq = d_in[5 * p + 3];
        const void* wo = d_in[5 * p + 4];
        prm.x[p] = (const __nv_bfloat16*)x;
        make_map(encode, &prm.k[p], kc, (uint64_t)kB * kH * kS, kDH, 64);
        make_map(encode, &prm.v[p], vc, (uint64_t)kB * kH * kS, kDH, 64);
        make_map(encode, &prm.wq[p], wq, kD, (uint64_t)kH * kDH, 128);
        make_map(encode, &prm.wo[p], wo, (uint64_t)kH * kDH, kD, 128);
    }
    prm.out = (__nv_bfloat16*)d_out;
    fused_decode_kernel<<<kNumCtas, kThreads, kSmemAlloc>>>(prm);
}
```
